```python
import torch

def _softmax(x, axis=-1):
    return torch.softmax(x, dim=axis)

def _gelu(x):
    return torch.nn.functional.gelu(x, approximate='tanh')

def _silu(x):
    return torch.nn.functional.silu(x)

def _sigmoid(x):
    return torch.sigmoid(x)

def _layernorm(x, axis=-1, eps=1e-05):
    m = x.mean(dim=axis, keepdim=True)
    v = x.var(dim=axis, keepdim=True, unbiased=False)
    return (x - m) / torch.sqrt(v + eps)

def _scatter_add(tgt, idx, src, axis=0):
    return tgt.clone().index_add_(axis, idx, src)

def _segment_sum(src, seg, n):
    out = torch.zeros((n,) + src.shape[1:], dtype=src.dtype)
    return out.index_add_(0, seg, src)

def _pad(x, pw):
    flat = tuple((v for pair in reversed(pw) for v in pair))
    return torch.nn.functional.pad(x, flat)
kernel_name = 'interleave_layers__memory_aug_recurrent_mem_tr__glu_gated_swiglu__prompt'

def setup_inputs():

    _w = lambda a: (lambda t: t.to(torch.bfloat16) if t.is_floating_point() else t)(torch.as_tensor(a))

    def _A_setup():
        B, S, Dm = (1, 2048, 576)
        H, Dh = (32, 128)
        M, seg = (8, 32)
        seg = min(seg, S)
        S = S // seg * seg
        return {'x': _w((lambda *s: torch.randn(*s, dtype=torch.bfloat16) * 0.05)(B, S, Dm)), 'mem0': _w((lambda *s: torch.randn(*s, dtype=torch.bfloat16) * 0.2)(B, M, Dm)), 'Wq': _w((lambda *s: torch.randn(*s, dtype=torch.bfloat16) * 1.6)(Dm, H, Dh) * Dm ** (-0.5)), 'Wk': _w((lambda *s: torch.randn(*s, dtype=torch.bfloat16) * 1.6)(Dm, H, Dh) * Dm ** (-0.5)), 'Wv': _w((lambda *s: torch.randn(*s, dtype=torch.bfloat16) * 0.2)(Dm, H, Dh) * Dm ** (-0.5)), 'Wo': _w((lambda *s: torch.randn(*s, dtype=torch.bfloat16) * 0.2)(H, Dh, Dm) * (H * Dh) ** (-0.5)), 'seg_len': seg}
    _A_in = _A_setup()

    def _B_setup():
        B, S, D, F = (1, 2048, 576, 4608)
        return {'x': _w((lambda *s: torch.randn(*s, dtype=torch.bfloat16) * 0.05)(B, S, D)), 'w1': _w((lambda *s: torch.randn(*s, dtype=torch.bfloat16) * 0.2)(D, F) * (2.0 / D) ** 0.5), 'w3': _w((lambda *s: torch.randn(*s, dtype=torch.bfloat16) * 0.2)(D, F) * (2.0 / D) ** 0.5), 'w2': _w((lambda *s: torch.randn(*s, dtype=torch.bfloat16) * 0.2)(F, D) * (2.0 / F) ** 0.5)}
    _B_in = _B_setup()
    return {'A_x': _A_in['x'], 'A_mem0': _A_in['mem0'], 'A_Wq': _A_in['Wq'], 'A_Wk': _A_in['Wk'], 'A_Wv': _A_in['Wv'], 'A_Wo': _A_in['Wo'], 'A_seg_len': _A_in['seg_len'], 'B_x': _B_in['x'], 'B_w1': _B_in['w1'], 'B_w3': _B_in['w3'], 'B_w2': _B_in['w2']}

def reference(A_x, A_mem0, A_Wq, A_Wk, A_Wv, A_Wo, A_seg_len, B_x, B_w1, B_w3, B_w2):

    def _A_ref(x, mem0, Wq, Wk, Wv, Wo, seg_len):
        B, S, Dm = x.shape
        H, Dh = (Wq.shape[1], Wq.shape[2])
        M = mem0.shape[1]
        scale = Dh ** (-0.5)
        n_seg = S // seg_len
        L = M + seg_len
        idx = torch.arange(L)
        mask = (idx[:, None] < M) | (idx[:, None] >= idx[None, :])
        mem = mem0
        outs = []
        for s in range(n_seg):
            xs = x[:, s * seg_len:(s + 1) * seg_len, :].clone()
            h = torch.concatenate([mem, xs], axis=1)
            q = torch.einsum('btd,dhe->bhte', h, Wq)
            k = torch.einsum('btd,dhe->bhte', h, Wk)
            v = torch.einsum('btd,dhe->bhte', h, Wv)
            scores = torch.einsum('bhqe,bhke->bhqk', q, k) * scale
            scores = torch.where(mask[None, None], scores, -1000000000.0)
            p = _softmax(scores, axis=-1)
            o = torch.einsum('bhqk,bhke->bhqe', p, v)
            o = torch.einsum('bhte,hed->btd', o, Wo)
            mem = o[:, :M, :].clone()
            outs.append(o[:, M:, :])
        return torch.concatenate(outs, axis=1)

    def _B_ref(x, w1, w3, w2):
        gate = torch.einsum('bsd,df->bsf', x, w1)
        up = torch.einsum('bsd,df->bsf', x, w3)
        h = _silu(gate) * up
        out = torch.einsum('bsf,fd->bsd', h, w2)
        return out
    x = A_x
    x = x + _A_ref(_layernorm(x, axis=-1), A_mem0, A_Wq, A_Wk, A_Wv, A_Wo, A_seg_len)
    x = x + _B_ref(_layernorm(x, axis=-1), B_w1, B_w3, B_w2)
    x = x + _A_ref(_layernorm(x, axis=-1), A_mem0, A_Wq, A_Wk, A_Wv, A_Wo, A_seg_len)
    x = x + _B_ref(_layernorm(x, axis=-1), B_w1, B_w3, B_w2)
    return x
```

```cpp
#include <cuda_runtime.h>
#include <cuda_bf16.h>
#include <cuda.h>
#include <stdint.h>

typedef __nv_bfloat16 bf16;

namespace {

constexpr int S_TOK = 2048, DM = 576, NH = 32, FF = 4608, NSEG = 64;
#define LAG 7
#define RING 8
static_assert(RING > LAG && (RING & (RING - 1)) == 0, "ring slots are only protected by the dataflow cycle");
constexpr int NSTEP = NSEG + LAG;
constexpr int NENG = 64, NF1 = 36, NWO = 15, NF2 = 15, NGRID = 132;
constexpr int CTA_F1 = NENG, CTA_WO = CTA_F1 + NF1, CTA_F2 = CTA_WO + NWO, CTA_SP = CTA_F2 + NF2;
constexpr int NTHREADS = 384;
constexpr int XIMG = 9 * 8192;
constexpr int LN0_SPLIT = 1056;
#define RS_DELAY 700
#define RS_SKEW 60
#define RS_DELAY0 300
#define AG_DELAY 700
#define QK_LEAD 30
#define GB1 2
#define GB2 2
#define G_DELAY 9000
constexpr int SPIN_LIMIT = 4000000;

enum { F_XE = 0, F_XF, F_PW, F_PF, F_O, F_H = F_O + 5, F_DONE = F_H + 5, F_COUNT };
__device__ uint32_t g_flag[F_COUNT][NSTEP + 2][8];
__device__ uint32_t g_epoch;
__device__ __align__(1024) uint8_t g_xe[NSTEP * XIMG];
__device__ __align__(1024) uint8_t g_xf[RING * XIMG];
__device__ __align__(1024) uint8_t g_o[RING * 64 * 8192];
__device__ __align__(1024) uint8_t g_h[RING * FF * 128];
__device__ __align__(1024) uint8_t g_part[2][RING * 5 * 64 * 1152];
__device__ __align__(1024) uint8_t g_x1[RING * 64 * 1152];
__device__ __align__(1024) uint8_t g_res[2][S_TOK * 1152];
__device__ __align__(1024) uint8_t g_rs[2 * NENG * 10240];
__device__ __align__(1024) uint8_t g_ag[2 * 18432];

struct Params {
    CUtensorMap tmWq, tmWk, tmWv, tmWo, tmW1, tmW3, tmW2, tmRs, tmR9;
    uint64_t d128, d64, dMem, dOm, dQ, dK;
    const bf16* x;
    const bf16* mem0;
    bf16* out;
};

constexpr int SM_TOTAL = 232448;
constexpr int SM_BAR = SM_TOTAL - 512;
constexpr int KRQ = 34, KRV = 35;
constexpr int E_WK = 0;
constexpr int E_WO = E_WK + 36 * 2048;
constexpr int E_WQ = E_WO + 36 * 2048;
constexpr int E_WV = E_WQ + (36 - KRQ) * 2048;
constexpr int E_RING = E_WV + (36 - KRV) * 2048;
constexpr int E_MEM = E_RING + 2 * 8192;
constexpr int E_OM = E_MEM + 18432;
constexpr int TG = 2064;
constexpr int E_T = E_OM + 4096;
constexpr int E_QX = E_T, E_QM = E_T + TG, E_KX = E_T + 3 * TG, E_KM = E_T + 11 * TG, E_VX = E_T + 8 * TG, E_VM = E_T + 13 * TG;
constexpr int E_RS = E_T + 16384;
constexpr int E_BAR = E_T + 15 * TG;
constexpr int E_R2 = SM_TOTAL - 8192;
constexpr int SG = 1056, E_OUT = SM_TOTAL - 7 * SG - 1024;
static_assert(E_BAR + 512 <= E_OUT && E_RING % 1024 == 0 && E_MEM % 1024 == 0 && E_OM % 1024 == 0 && E_T % 1024 == 0 && E_R2 % 1024 == 0, "engine smem");
constexpr int E_ST1 = 19;
__host__ __device__ constexpr int e_stage(int j) { return j < 34 ? E_RING + j * 2048 : E_R2 + (j - 34) * 2048; }
static_assert(E_RING + 34 * 2048 <= E_BAR && 2 * E_ST1 <= 38, "staging");
__host__ __device__ constexpr int x_slot(int c) {
    return c < 2 ? E_RING + c * 8192 : c < 4 ? E_MEM + (c - 2) * 8192 : c == 4 ? E_R2 : c < 7 ? E_T + (c - 5) * 8192 : E_RING + (c - 7) * 8192;
}
enum { B_XF = 0, B_WL = 9, B_WS, B_QK, B_V, B_OM, B_E01, B_TF, B_RF = 49, B_PD, B_MF, B_AG, B_FULL = 0, B_EMPTY = 16, B_PUB = 32 };
enum { NB_ALL = 1, NB_MA, NB_MB, NB_QKI, NB_SI, NB_PVI, NB_WIA, NB_WIB, NB_XI, NB_C, NB_WG0, NB_WG1 };
constexpr int SM_EPOCH = SM_BAR + 384, E_EPOCH = E_BAR + 384;

#define SPIN_CHECK(n, code) asm volatile("{.reg .pred p; setp.gt.s32 p, %0, %1; @p st.global.u32 [%2], %0;}" :: "r"(++(n)), "n"(SPIN_LIMIT), "l"(0ull))

#define EV(thr, k, v)
#define ES(thr, k)
#define EFLUSH(step)
#define TS(thr, step, k)
#define TV(thr, step, k, v)

__device__ __forceinline__ uint32_t smem_u32(const void* p) { return (uint32_t)__cvta_generic_to_shared(p); }
__device__ __forceinline__ uint32_t mapa(uint32_t a, uint32_t r) {
    uint32_t o; asm("mapa.shared::cluster.u32 %0, %1, %2;" : "=r"(o) : "r"(a), "r"(r)); return o;
}
__device__ __forceinline__ void mbar_init(uint32_t b, uint32_t cnt) {
    asm volatile("mbarrier.init.shared::cta.b64 [%0], %1;" :: "r"(b), "r"(cnt) : "memory");
}
__device__ __forceinline__ void mbar_arrive(uint32_t b) {
    asm volatile("mbarrier.arrive.shared::cta.b64 _, [%0];" :: "r"(b) : "memory");
}
__device__ __forceinline__ void mbar_arrive_remote(uint32_t b) {
    asm volatile("mbarrier.arrive.relaxed.cluster.shared::cluster.b64 _, [%0];" :: "r"(b) : "memory");
}
__device__ __forceinline__ void mbar_expect(uint32_t b, uint32_t bytes) {
    asm volatile("mbarrier.arrive.expect_tx.shared::cta.b64 _, [%0], %1;" :: "r"(b), "r"(bytes) : "memory");
}
#define MBAR_WAIT(SEM) asm volatile("{.reg .pred p; W: mbarrier.try_wait.parity" SEM ".shared::cta.b64 p, [%0], %1; @!p bra W;}" :: "r"(b), "r"(par) : "memory")
__device__ __forceinline__ void mbar_wait(uint32_t b, uint32_t par) { MBAR_WAIT(""); }
__device__ __forceinline__ void mbar_wait_cl(uint32_t b, uint32_t par) {
    MBAR_WAIT(".relaxed.cluster");
    asm volatile("fence.acquire.sync_restrict::shared::cluster.cluster;" ::: "memory");
}
__device__ __forceinline__ void nbar_sync(int id, int n) { asm volatile("bar.sync %0, %1;" :: "r"(id), "r"(n) : "memory"); }
__device__ __forceinline__ void nbar_arrive(int id, int n) { asm volatile("bar.arrive %0, %1;" :: "r"(id), "r"(n) : "memory"); }
__device__ __forceinline__ void cluster_sync_all() {
    asm volatile("barrier.cluster.arrive.release.aligned; barrier.cluster.wait.acquire.aligned;" ::: "memory");
}
__device__ __forceinline__ void fence_async_smem() { asm volatile("fence.proxy.async.shared::cta;" ::: "memory"); }
__device__ __forceinline__ void fence_async_glb() { asm volatile("fence.proxy.async.global;" ::: "memory"); }
__device__ __forceinline__ void fence_rel_gpu() { asm volatile("fence.release.gpu;" ::: "memory"); }
__device__ __forceinline__ void fence_acq_gpu() { asm volatile("fence.acquire.gpu;" ::: "memory"); }
__device__ __forceinline__ int fresh_tid() { int t; asm volatile("mov.u32 %0, %%tid.x;" : "=r"(t)); return t; }
__device__ __forceinline__ int fresh_bid() { int t; asm volatile("mov.u32 %0, %%ctaid.x;" : "=r"(t)); return t; }
__device__ __forceinline__ uint32_t keep(uint32_t v) { asm volatile("" : "+r"(v)); return v; }
__device__ __forceinline__ uint32_t opaque(uint32_t v) { return __shfl_xor_sync(~0u, v, 0); }
__device__ __forceinline__ bool elect() {
    uint32_t p; asm volatile("{.reg .pred p; elect.sync _|p, 0xffffffff; selp.u32 %0, 1, 0, p;}" : "=r"(p)); return p;
}
__device__ __forceinline__ uint32_t clock32() { uint32_t t; asm volatile("mov.u32 %0, %%clock;" : "=r"(t) :: "memory"); return t; }
__device__ __forceinline__ void red_add_u32(uint32_t* p, uint32_t v) {
    asm volatile("red.relaxed.gpu.global.add.u32 [%0], %1;" :: "l"(p), "r"(v) : "memory");
}
__device__ __forceinline__ uint32_t ld_rlx(const uint32_t* p) {
    uint32_t v; asm volatile("ld.relaxed.gpu.global.u32 %0, [%1];" : "=r"(v) : "l"(p) : "memory"); return v;
}
__device__ __forceinline__ void st_rlx128(void* p, uint4 v) {
    asm volatile("{.reg .b128 r; .reg .b64 a, b; mov.b64 a, {%1,%2}; mov.b64 b, {%3,%4}; mov.b128 r, {a, b}; st.relaxed.gpu.global.b128 [%0], r;}"
                 :: "l"(p), "r"(v.x), "r"(v.y), "r"(v.z), "r"(v.w) : "memory");
}
__device__ __forceinline__ void st_rlx64(void* p, uint32_t a, uint32_t b) {
    asm volatile("{.reg .b64 r; mov.b64 r, {%1,%2}; st.relaxed.gpu.global.b64 [%0], r;}" :: "l"(p), "r"(a), "r"(b) : "memory");
}
__device__ __forceinline__ void st_rlx32(void* p, uint32_t v) { asm volatile("st.relaxed.gpu.global.u32 [%0], %1;" :: "l"(p), "r"(v) : "memory"); }
__device__ __forceinline__ uint32_t xor_or(uint32_t a, uint32_t b, uint32_t t) {
    uint32_t d; asm("lop3.b32 %0, %1, %2, %3, 0x7E;" : "=r"(d) : "r"(a), "r"(b), "r"(t)); return d;
}
__device__ __forceinline__ uint32_t or_bit0(uint32_t a, uint32_t b) {
    uint32_t d; asm("lop3.b32 %0, %1, %2, 1, 0xA8;" : "=r"(d) : "r"(a), "r"(b)); return d;
}
__device__ __forceinline__ uint4 ld_l2_128(const void* p) {
    uint4 v;
    asm volatile("ld.relaxed.gpu.global.v4.u32 {%0,%1,%2,%3}, [%4];" : "=r"(v.x), "=r"(v.y), "=r"(v.z), "=r"(v.w) : "l"(p) : "memory");
    return v;
}
__device__ __forceinline__ void stg128(void* p, uint4 v) {
    asm volatile("st.global.v4.b32 [%0], {%1,%2,%3,%4};" :: "l"(p), "r"(v.x), "r"(v.y), "r"(v.z), "r"(v.w) : "memory");
}
__device__ __forceinline__ void stg64(void* p, uint32_t a, uint32_t b) {
    asm volatile("st.global.v2.b32 [%0], {%1,%2};" :: "l"(p), "r"(a), "r"(b) : "memory");
}
__device__ __forceinline__ void st_async128(uint32_t a, uint4 v, uint32_t mb) {
    asm volatile("st.async.shared::cluster.mbarrier::complete_tx::bytes.v4.b32 [%0], {%1,%2,%3,%4}, [%5];"
                 :: "r"(a), "r"(v.x), "r"(v.y), "r"(v.z), "r"(v.w), "r"(mb) : "memory");
}
__device__ __forceinline__ void st_async32(uint32_t a, uint32_t v, uint32_t mb) {
    asm volatile("st.async.shared::cluster.mbarrier::complete_tx::bytes.b32 [%0], %1, [%2];" :: "r"(a), "r"(v), "r"(mb) : "memory");
}
__device__ __forceinline__ void sts128(uint32_t a, uint4 v) {
    asm volatile("st.shared.v4.b32 [%0], {%1,%2,%3,%4};" :: "r"(a), "r"(v.x), "r"(v.y), "r"(v.z), "r"(v.w) : "memory");
}
__device__ __forceinline__ void sts32(uint32_t a, uint32_t v) { asm volatile("st.shared.b32 [%0], %1;" :: "r"(a), "r"(v) : "memory"); }
__device__ __forceinline__ uint32_t lds32(uint32_t a) { uint32_t v; asm volatile("ld.shared.b32 %0, [%1];" : "=r"(v) : "r"(a) : "memory"); return v; }
__device__ __forceinline__ uint2 lds64(uint32_t a) {
    uint2 v; asm volatile("ld.shared.v2.b32 {%0,%1}, [%2];" : "=r"(v.x), "=r"(v.y) : "r"(a) : "memory"); return v;
}
__device__ __forceinline__ uint4 lds128(uint32_t a) {
    uint4 v; asm volatile("ld.shared.v4.b32 {%0,%1,%2,%3}, [%4];" : "=r"(v.x), "=r"(v.y), "=r"(v.z), "=r"(v.w) : "r"(a) : "memory"); return v;
}
__device__ __forceinline__ void bulk_g2s(uint32_t dst, const void* src, uint32_t bytes, uint32_t mb) {
    asm volatile("cp.async.bulk.shared::cluster.global.mbarrier::complete_tx::bytes [%0], [%1], %2, [%3];"
                 :: "r"(dst), "l"(src), "r"(bytes), "r"(mb) : "memory");
}
__device__ __forceinline__ void bulk_s2peer(uint32_t dst, uint32_t src, uint32_t bytes, uint32_t mb) {
    asm volatile("cp.async.bulk.shared::cluster.shared::cta.mbarrier::complete_tx::bytes [%0], [%1], %2, [%3];"
                 :: "r"(dst), "r"(src), "r"(bytes), "r"(mb) : "memory");
}
__device__ __forceinline__ void tma_2d(uint32_t dst, const CUtensorMap* tm, int x, int y, uint32_t mb) {
    asm volatile("cp.async.bulk.tensor.2d.shared::cluster.global.mbarrier::complete_tx::bytes [%0], [%1, {%2,%3}], [%4];"
                 :: "r"(dst), "l"(tm), "r"(x), "r"(y), "r"(mb) : "memory");
}
__device__ __forceinline__ void tma_w(uint32_t dst, const CUtensorMap* tm, int ks, int grp, uint32_t mb) {
    asm volatile("cp.async.bulk.tensor.3d.shared::cluster.global.mbarrier::complete_tx::bytes [%0], [%1, {%2,%3,%4}], [%5];"
                 :: "r"(dst), "l"(tm), "r"(0), "r"(ks * 16), "r"(grp), "r"(mb) : "memory");
}
__device__ __forceinline__ void tma_w_prefetch(const CUtensorMap* tm, int ks, int grp) {
    asm volatile("cp.async.bulk.prefetch.tensor.3d.L2.global [%0, {%1,%2,%3}];" :: "l"(tm), "r"(0), "r"(ks * 16), "r"(grp) : "memory");
}
__device__ __forceinline__ void ldsm4t(uint32_t* r, uint32_t a) {
    asm volatile("ldmatrix.sync.aligned.m8n8.x4.trans.shared.b16 {%0,%1,%2,%3}, [%4];"
                 : "=r"(r[0]), "=r"(r[1]), "=r"(r[2]), "=r"(r[3]) : "r"(a) : "memory");
}
__device__ __forceinline__ uint32_t movm(uint32_t a) {
    uint32_t d; asm volatile("movmatrix.sync.aligned.m8n8.trans.b16 %0, %1;" : "=r"(d) : "r"(a)); return d;
}
__device__ __forceinline__ uint32_t pack2(float lo, float hi) {
    uint32_t d; asm("cvt.rn.bf16x2.f32 %0, %1, %2;" : "=r"(d) : "f"(hi), "f"(lo)); return d;
}
__device__ __forceinline__ float bf_lo(uint32_t w) { return __uint_as_float(w << 16); }
__device__ __forceinline__ float bf_hi(uint32_t w) { return __uint_as_float(w & 0xffff0000u); }
__device__ __forceinline__ float ex2(float x) { float y; asm("ex2.approx.ftz.f32 %0, %1;" : "=f"(y) : "f"(x)); return y; }
__device__ __forceinline__ float rcp(float x) { float y; asm("rcp.approx.ftz.f32 %0, %1;" : "=f"(y) : "f"(x)); return y; }
__device__ __forceinline__ void spin_cycles(int c) {
    uint32_t t0, t1;
    asm volatile("mov.u32 %0, %%clock;" : "=r"(t0));
    do { asm volatile("mov.u32 %0, %%clock;" : "=r"(t1)); } while ((int)(t1 - t0) < c);
}
template <int N> __device__ __forceinline__ void reg_inc() { asm volatile("setmaxnreg.inc.sync.aligned.u32 %0;" :: "n"(N)); }
template <int N> __device__ __forceinline__ void reg_dec() { asm volatile("setmaxnreg.dec.sync.aligned.u32 %0;" :: "n"(N)); }

__device__ __forceinline__ void flag_poll(const uint32_t* f, uint32_t target) {
    int n = 0;
    while ((int)(ld_rlx(f) - target) < 0) {
        __nanosleep(20);
        SPIN_CHECK(n, (int)(f - &g_flag[0][0][0]) / 8);
    }
}
__device__ __forceinline__ void flag_signal(uint32_t* f) {
    fence_rel_gpu();
    red_add_u32(f, 1);
}

constexpr uint32_t SM_BASE = 1024;
__host__ __device__ constexpr uint64_t mkdesc(uint32_t off, uint32_t lbo, uint32_t sbo, uint32_t swz) {
    return (uint64_t)((SM_BASE + off) >> 4) | ((uint64_t)(lbo >> 4) << 16) | ((uint64_t)(sbo >> 4) << 32) | ((uint64_t)swz << 62);
}
__device__ __forceinline__ void dmove(uint64_t& d, int delta) { asm volatile("add.s64 %0, %0, %1;" : "+l"(d) : "l"((long long)delta)); }
__device__ __forceinline__ void wg_fence() { asm volatile("wgmma.fence.sync.aligned;" ::: "memory"); }
__device__ __forceinline__ void wg_commit() { asm volatile("wgmma.commit_group.sync.aligned;" ::: "memory"); }
template <int N> __device__ __forceinline__ void wg_wait() { asm volatile("wgmma.wait_group.sync.aligned %0;" :: "n"(N) : "memory"); }

#define F4(c, d, o) c(d[o]), c(d[o + 1]), c(d[o + 2]), c(d[o + 3])
#define F8(c, d, o) F4(c, d, o), F4(c, d, o + 4)
#define F32(c, d, o) F8(c, d, o), F8(c, d, o + 8), F8(c, d, o + 16), F8(c, d, o + 24)
#define L8 "%0,%1,%2,%3,%4,%5,%6,%7"
#define L20 L8 ",%8,%9,%10,%11,%12,%13,%14,%15,%16,%17,%18,%19"
#define L32 L20 ",%20,%21,%22,%23,%24,%25,%26,%27,%28,%29,%30,%31"
#define L64 L32 ",%32,%33,%34,%35,%36,%37,%38,%39,%40,%41,%42,%43,%44,%45,%46,%47,%48,%49,%50,%51,%52,%53,%54,%55,%56,%57,%58,%59,%60,%61,%62,%63"
#define O8(c) F8(c, d, 0)
#define O20(c) F8(c, d, 0), F8(c, d, 8), F4(c, d, 16)
#define O32(c) F32(c, d, 0)
#define O64(c) F32(c, d, 0), F32(c, d, 32)
#define WG_BOTH(TXT_PRE, TXT_POST, OUTS, ...)                                                   \
    if (acc > 0) asm volatile(TXT_PRE "1" TXT_POST : OUTS("+f") : __VA_ARGS__);                 \
    else if (acc < 0) asm volatile(TXT_PRE "0" TXT_POST : OUTS("+f") : __VA_ARGS__);            \
    else asm volatile(TXT_PRE "0" TXT_POST : OUTS("=f") : __VA_ARGS__)
#define AREGS "r"(a[0]), "r"(a[1]), "r"(a[2]), "r"(a[3])
template <int TB> __device__ __forceinline__ void wg_rs16(float* d, const uint32_t* a, uint64_t db, int acc) {
    WG_BOTH("wgmma.mma_async.sync.aligned.m64n16k16.f32.bf16.bf16 {" L8 "}, {%8,%9,%10,%11}, %12, ", ", 1, 1, %13;", O8, AREGS, "l"(db), "n"(TB));
}
template <int TB> __device__ __forceinline__ void wg_ss16(float* d, uint64_t da, uint64_t db, int acc) {
    WG_BOTH("wgmma.mma_async.sync.aligned.m64n16k16.f32.bf16.bf16 {" L8 "}, %8, %9, ", ", 1, 1, 1, %10;", O8, "l"(da), "l"(db), "n"(TB));
}
template <int TB> __device__ __forceinline__ void wg_ss40(float* d, uint64_t da, uint64_t db, int acc) {
    WG_BOTH("wgmma.mma_async.sync.aligned.m64n40k16.f32.bf16.bf16 {" L20 "}, %20, %21, ", ", 1, 1, 1, %22;", O20, "l"(da), "l"(db), "n"(TB));
}
template <int TB> __device__ __forceinline__ void wg_rs64(float* d, const uint32_t* a, uint64_t db, int acc) {
    WG_BOTH("wgmma.mma_async.sync.aligned.m64n64k16.f32.bf16.bf16 {" L32 "}, {%32,%33,%34,%35}, %36, ", ", 1, 1, %37;", O32, AREGS, "l"(db), "n"(TB));
}
template <int TB> __device__ __forceinline__ void wg_ss64(float* d, uint64_t da, uint64_t db, int acc) {
    WG_BOTH("wgmma.mma_async.sync.aligned.m64n64k16.f32.bf16.bf16 {" L32 "}, %32, %33, ", ", 1, 1, 1, %34;", O32, "l"(da), "l"(db), "n"(TB));
}
template <int TB> __device__ __forceinline__ void wg_rs128(float* d, const uint32_t* a, uint64_t db, int acc) {
    WG_BOTH("wgmma.mma_async.sync.aligned.m64n128k16.f32.bf16.bf16 {" L64 "}, {%64,%65,%66,%67}, %68, ", ", 1, 1, %69;", O64, AREGS, "l"(db), "n"(TB));
}
__device__ __forceinline__ uint32_t frag_addr(uint32_t base) {
    const int tid = threadIdx.x, i = tid & 7, j = (tid >> 3) & 3, warp = (tid >> 5) & 3;
    return base + ((j >> 1) * 8 + i) * 128 + ((((warp << 1) + (j & 1)) ^ i) << 4);
}

constexpr float SM_SCALE = 0.08838834764831845f;
constexpr float LOG2E = 1.4426950408889634f;

__device__ __forceinline__ void add8(float* f, uint4 a) {
    f[0] += bf_lo(a.x); f[1] += bf_hi(a.x); f[2] += bf_lo(a.y); f[3] += bf_hi(a.y);
    f[4] += bf_lo(a.z); f[5] += bf_hi(a.z); f[6] += bf_lo(a.w); f[7] += bf_hi(a.w);
}
__device__ __forceinline__ void ln_row(const Params& P, const int MODE, int step, int n  ) {
    const int lane = fresh_tid() & 31, l = lane < 24 ? lane : 0;
    const int tok = (n < 32 ? step : step - LAG) * 32 + (n & 31), slot = step & (RING - 1);
    const uint32_t nat = (l >> 1) * 32 + (l & 1) * 8;
    uint4 xw[3];
    if (MODE == 0) {
        const uint8_t* src = (const uint8_t*)P.x + tok * 1152 + nat;
#pragma unroll
        for (int k = 0; k < 3; k++) {
            const uint2 a = __ldg((const uint2*)(src + k * 384)), b = __ldg((const uint2*)(src + k * 384 + 16));
            xw[k] = make_uint4(a.x, b.x, a.y, b.y);
        }
    } else {
        const uint8_t* res = (MODE == 1 ? g_res[n >> 5] + tok * 1152 : g_x1 + (slot * 64 + n) * 1152) + l * 16;
        const uint8_t* src = g_part[MODE >> 1] + (slot * 5 * 64 + n) * 1152 + l * 16;
        uint4 a[15];
#pragma unroll
        for (int j = 0; j < 15; j++) a[j] = ld_l2_128(src + (j / 3) * (64 * 1152) + (j % 3) * 384);
#pragma unroll
        for (int k = 0; k < 3; k++) xw[k] = ld_l2_128(res + k * 384);
#pragma unroll
        for (int k = 0; k < 3; k++) {
            float f[8] = {0.f, 0.f, 0.f, 0.f, 0.f, 0.f, 0.f, 0.f};
#pragma unroll
            for (int j = 0; j < 5; j++) add8(f, a[3 * j + k]);
            add8(f, xw[k]);
            xw[k] = make_uint4(pack2(f[0], f[1]), pack2(f[2], f[3]), pack2(f[4], f[5]), pack2(f[6], f[7]));
        }
    }
    if (MODE == 3) {
        if (lane < 24) {
            uint8_t* d = (uint8_t*)P.out + tok * 1152 + nat;
#pragma unroll
            for (int k = 0; k < 3; k++) { stg64(d + k * 384, xw[k].x, xw[k].z); stg64(d + k * 384 + 16, xw[k].y, xw[k].w); }
        }
        return;
    }
    if (lane < 24) {
        uint8_t* d = (MODE == 1 ? g_x1 + (slot * 64 + n) * 1152 : g_res[MODE >> 1] + tok * 1152) + l * 16;
#pragma unroll
        for (int k = 0; k < 3; k++) stg128(d + k * 384, xw[k]);
    }
    const float shift = bf_lo(__shfl_sync(~0u, xw[0].x, 0));
    float f[24];
#pragma unroll
    for (int j = 0; j < 24; j++) f[j] = -shift;
#pragma unroll
    for (int k = 0; k < 3; k++) add8(&f[k * 8], xw[k]);
    float s = 0.f, q = 0.f;
#pragma unroll
    for (int j = 0; j < 24; j++) { s += f[j]; q += f[j] * f[j]; }
    if (lane >= 24) s = q = 0.f;
#pragma unroll
    for (int o = 16; o; o >>= 1) { s += __shfl_xor_sync(~0u, s, o); q += __shfl_xor_sync(~0u, q, o); }
    const float mean = s * (1.f / DM);
    const float rstd = rsqrtf(fmaxf(q * (1.f / DM) - mean * mean, 0.f) + 1e-5f);
    if (lane < 24) {
        const int tau = n & 31, row = ((tau >> 1) & 3) * 8 + (tau >> 3) * 2 + (tau & 1) + (MODE == 2 ? 32 : n & 32);
        uint8_t* d = (MODE == 1 ? g_xf + slot * XIMG : g_xe + (MODE == 2 ? step + LAG : step) * XIMG) + (l >> 3) * 8192 + row * 128 + (l & 1) * 8;
        const uint32_t c0 = ((l & 6) ^ (row & 7)) << 4;
#pragma unroll
        for (int k = 0; k < 3; k++) {
            const float* g = &f[8 * k];
            stg64(d + k * 24576 + c0, pack2((g[0] - mean) * rstd, (g[1] - mean) * rstd), pack2((g[4] - mean) * rstd, (g[5] - mean) * rstd));
            stg64(d + k * 24576 + (c0 ^ 16), pack2((g[2] - mean) * rstd, (g[3] - mean) * rstd), pack2((g[6] - mean) * rstd, (g[7] - mean) * rstd));
        }
    }
}
__device__ __forceinline__ void warp_signal(uint32_t* f) {
    __syncwarp();
    if ((threadIdx.x & 31) == 0) flag_signal(f);
}
__device__ __forceinline__ void warp_wait(const uint32_t* f, uint32_t target) {
    if ((threadIdx.x & 31) == 0) { flag_poll(f, target); fence_acq_gpu(); }
    __syncwarp();
}
__device__ __forceinline__ void ln_first(const Params& P, int row0, int row1, int stride) {
#pragma unroll 1
    for (int row = row0; row < row1; row += stride) {
        ln_row(P, 0, row >> 5, row & 31);
        warp_signal(g_flag[F_XE][row >> 5]);
    }
}

template <int KR, int WG>
__device__ __forceinline__ void load_wregs(uint32_t (&w)[KR][4], uint32_t sb) {
    const uint32_t base = frag_addr(sb);
    mbar_wait(sb + E_BAR + B_WL * 8, 0);
#pragma unroll
    for (int ks = 0; ks < E_ST1; ks++) ldsm4t(w[ks], base + e_stage(WG * E_ST1 + ks));
    nbar_sync(NB_ALL, NTHREADS);
    mbar_wait(sb + E_BAR + B_WL * 8, 1);
#pragma unroll
    for (int ks = E_ST1; ks < KR; ks++) ldsm4t(w[ks], base + e_stage(WG * E_ST1 + ks - E_ST1));
    cluster_sync_all();
    mbar_wait(sb + E_BAR + B_WS * 8, 0);
}
__host__ __device__ constexpr int m_pos(int tile) { return tile == 8 ? 0 : 1 + 2 * (tile & 3) + (tile >> 2); }
__host__ __device__ constexpr int m_off(int ks) { return m_pos(ks >> 2) * 128 + (ks & 3) * 16; }
template <int KR, bool LEAD>
__device__ __forceinline__ void proj_mem(const Params& P, float* d, const uint32_t (&w)[KR][4], uint32_t wss) {
    uint64_t db = P.dMem + m_off(35);
    wg_fence();
#pragma unroll
    for (int ks = 35; ks >= 0; ks--) {
        if (LEAD && 35 - ks == QK_LEAD) nbar_arrive(NB_QKI, NTHREADS);
        if (ks < KR) wg_rs16<1>(d, w[ks < KR ? ks : 0], db, ks < 35);
        else wg_ss16<1>(d, mkdesc(wss + (ks - KR) * 2048, 1024, 1024, 1), db, ks < 35);
        if (ks > 0) dmove(db, m_off(ks - 1) - m_off(ks));
    }
    wg_commit();
}
template <int KR, bool WITHK>
__device__ __forceinline__ void proj_x(uint64_t& db, uint64_t& dak, float* d, float* dk, const uint32_t (&w)[KR][4], uint32_t wss, int c) {
#pragma unroll
    for (int kk = 0; kk < 4; kk++) {
        const int ks = c * 4 + kk;
        if (ks < KR) wg_rs64<0>(d, w[ks < KR ? ks : 0], db, ks > 0);
        else wg_ss64<0>(d, mkdesc(wss + (ks - KR) * 2048, 1024, 1024, 1), db, ks > 0);
        if (WITHK) wg_ss64<0>(dk, dak, db, ks > 0);
        if (ks < 35) {
            dmove(db, kk < 3 ? 2 : (x_slot(c + 1) - x_slot(c)) / 16 - 6);
            if (WITHK) dmove(dak, kk < 3 ? 128 : (m_pos(c + 1) - m_pos(c)) * 512 - 384);
        }
    }
}
__device__ __forceinline__ void x_wait(uint32_t sb, int c, uint32_t par) {
    if (c == 0 || c == 2 || c == 4 || c == 5 || c == 7) mbar_wait(sb + E_BAR + (B_XF + c) * 8, par);
    wg_fence();
}
template <bool VPERM> __device__ __forceinline__ uint32_t tile_row(int tid, int rank) {
    const int w = (tid >> 5) & 3, g = (tid >> 2) & 7;
    return (rank * 64 + (VPERM ? (w >> 1) * 32 + (g >> 1) * 8 + (w & 1) * 4 + (g & 1) : w * 16 + g)) * 16;
}
template <bool VPERM>
__device__ __forceinline__ void put_mem(const float* d, uint32_t a, int rank, uint32_t peer_off, uint32_t mb) {
    const uint32_t p0 = pack2(d[0], d[1]), p1 = pack2(d[2], d[3]), p2 = pack2(d[4], d[5]), p3 = pack2(d[6], d[7]);
    constexpr int R = VPERM ? 32 : 128;
    st_async32(a + peer_off, rank ? p0 : p2, mb + peer_off);
    st_async32(a + R + peer_off, rank ? p1 : p3, mb + peer_off);
    sts32(a, rank ? p2 : p0);
    sts32(a + R, rank ? p3 : p1);
}
#define XCOL(c) "r"(pack2(e[16 * c], e[16 * c + 1])), "r"(pack2(e[16 * c + 4], e[16 * c + 5])), "r"(pack2(e[16 * c + 8], e[16 * c + 9])), "r"(pack2(e[16 * c + 12], e[16 * c + 13]))
__device__ __forceinline__ void put_xv(const float* d, uint32_t a, int rank, uint32_t peer_off, uint32_t mb) {
#pragma unroll
    for (int h = 0; h < 2; h++) {
        const float* e = d + 2 * h;
        asm volatile("{.reg .pred p; setp.ne.s32 p, %11, 0;"
                     "@p st.async.shared::cluster.mbarrier::complete_tx::bytes.v4.b32 [%9], {%0,%1,%2,%3}, [%10];"
                     "@!p st.async.shared::cluster.mbarrier::complete_tx::bytes.v4.b32 [%9], {%4,%5,%6,%7}, [%10];"
                     "@p st.shared.v4.b32 [%8], {%4,%5,%6,%7}; @!p st.shared.v4.b32 [%8], {%0,%1,%2,%3};}"
                     :: XCOL(0), XCOL(1), "r"(a + h * 32), "r"(a + h * 32 + peer_off), "r"(mb + peer_off), "r"(rank) : "memory");
    }
}
__device__ __forceinline__ void park_x(const float* d, uint32_t a0, uint32_t a1) {
#pragma unroll
    for (int h = 0; h < 2; h++) {
        const float* e = d + 2 * h;
        asm volatile("st.shared.v4.b32 [%8], {%0,%1,%2,%3}; st.shared.v4.b32 [%9], {%4,%5,%6,%7};"
                     :: XCOL(0), XCOL(1), "r"(a0 + h * 128), "r"(a1 + h * 128) : "memory");
    }
}
#undef XCOL
__device__ __forceinline__ void warp_arrive(uint32_t b) { __syncwarp(); if ((threadIdx.x & 31) == 0) mbar_arrive(b); }

__device__ __forceinline__ void x_load(uint32_t sb, const uint8_t* img, int c) {
    const uint32_t bytes = c == 4 ? 8192 : 16384;
    mbar_expect(sb + E_BAR + (B_XF + c) * 8, bytes);
    bulk_g2s(sb + x_slot(c), img + c * 8192, bytes, sb + E_BAR + (B_XF + c) * 8);
}
__device__ __forceinline__ void x_ready(int step, uint32_t e1) {
    const uint32_t target = e1 * 32 * ((step < NSEG) + (step >= LAG) + (step > 2 * LAG));
    int n = 0;
    while ((int)(ld_rlx(g_flag[F_XE][step]) - target) < 0) { SPIN_CHECK(n, 3); }
    fence_acq_gpu();
    fence_async_glb();
}

__device__ __forceinline__ void softmax_rows(const float* p, const float* q, uint32_t* pk, uint32_t* qk) {
    float mp = fmaxf(fmaxf(fmaxf(p[0], p[1]), fmaxf(p[2], p[3])), fmaxf(fmaxf(fmaxf(p[4], p[5]), fmaxf(p[6], p[7])), fmaxf(p[8], p[9])));
    float mq = fmaxf(fmaxf(q[0], q[1]), fmaxf(q[2], q[3]));
#pragma unroll
    for (int o = 1; o <= 2; o++) { mp = fmaxf(mp, __shfl_xor_sync(~0u, mp, o)); mq = fmaxf(mq, __shfl_xor_sync(~0u, mq, o)); }
    mp *= SM_SCALE * LOG2E;
    mq *= SM_SCALE * LOG2E;
#pragma unroll
    for (int j = 0; j < 5; j++) pk[j] = pack2(ex2(fmaf(p[2 * j], SM_SCALE * LOG2E, -mp)), ex2(fmaf(p[2 * j + 1], SM_SCALE * LOG2E, -mp)));
#pragma unroll
    for (int j = 0; j < 2; j++) qk[j] = pack2(ex2(fmaf(q[2 * j], SM_SCALE * LOG2E, -mq)), ex2(fmaf(q[2 * j + 1], SM_SCALE * LOG2E, -mq)));
}

__device__ __forceinline__ void engine_a(const Params& P, uint32_t sb) {
    const uint32_t bars = sb + E_BAR;
    uint32_t w[KRQ][4];
    load_wregs<KRQ, 0>(w, sb);
    const int rank = blockIdx.x & 1;
    const uint32_t peer_off = mapa(sb, rank ^ 1) - sb;
    const int tid = opaque(threadIdx.x);
    const bool warp0 = __shfl_sync(~0u, tid, 0) == 0, lane0 = (tid & 31) == 0;
    const uint32_t row = opaque(sb + tile_row<false>(tid, rank));
    const int dq = opaque((tid >> 2) - 2 * (tid & 3));
#pragma unroll 1
    for (int i = 0; i < NSTEP; i++) {
        {
            const uint32_t xp = i & 1;
            float xq[32], xk[32], d[8];
            uint64_t db = P.d128 + x_slot(0) / 16, dak = P.d128 + (E_WK / 16 + m_pos(0) * 512);
#define XA(c) x_wait(sb, c, xp); proj_x<KRQ, true>(db, dak, xq, xk, w, E_WQ, c); wg_commit()
            if (i > 0) nbar_sync(NB_WIA, 256);
            XA(0); XA(1); XA(2);
            wg_wait<1>();
            if (lane0) mbar_arrive(bars + B_E01 * 8);
            ES(0, 8);
            XA(3); XA(4);
            wg_wait<1>();
            if (lane0) mbar_arrive(bars + B_MF * 8);
            ES(0, 9);
            XA(5); XA(6); XA(7);
            wg_wait<1>();
            if (lane0) { mbar_arrive_remote(bars + B_TF * 8 + peer_off); mbar_arrive(bars + B_TF * 8); }
            XA(8);
#undef XA
            nbar_arrive(NB_XI, 256);
            const uint32_t t = keep(tid) & 3, own = row + t * (2 * TG), out = row - rank * 1024 + E_OUT + t * SG;
            ES(0, 10);
            mbar_wait(bars + B_TF * 8, xp);
            wg_wait<0>();
            park_x(xk, rank ? out : own + E_KX, rank ? own + E_KX : out);
            park_x(xq, rank ? out + 4 * SG : own + E_QX, rank ? own + E_QX : out + 4 * SG);
            fence_async_smem();
            __syncwarp();
            if (lane0) mbar_arrive(bars + B_RF * 8);
            ES(0, 11);
            nbar_sync(NB_MA, 256);
            proj_mem<KRQ, true>(P, d, w, E_WQ);
            wg_wait<0>();
            put_mem<false>(d, row + E_QM + t * 4, rank, peer_off, bars + B_QK * 8);
            __syncwarp();
            if (lane0) { mbar_expect(bars + B_QK * 8, (2048 + 8192) / 4); mbar_arrive(bars + B_PD * 8); }
        }
        const uint32_t par = i & 1;
        ES(0, 1);
        uint32_t pa[12];
        {
            float s[20];
            uint64_t da = P.dQ, db = P.dK;
            mbar_wait_cl(bars + B_QK * 8, par);
            fence_async_smem();
            ES(0, 2);
            wg_fence();
#pragma unroll
            for (int ks = 0; ks < 8; ks++) { wg_ss40<1>(s, da, db, ks > 0); if (ks < 7) { dmove(da, 16); dmove(db, 16); } }
            wg_commit();
            nbar_arrive(NB_SI, 256);
            wg_wait<0>();
            ES(0, 3);
            constexpr float MASKED = -1e9f / SM_SCALE;
            float p[10];
            uint32_t pk[5], qk[2];
#pragma unroll
            for (int j = 0; j < 10; j++) p[j] = (j >= 8 || (j >> 1) * 8 + (j & 1) <= dq) ? s[(j >> 1) * 4 + (j & 1)] : MASKED;
            const float q[4] = {p[0], p[1], p[8], p[9]};
#pragma unroll
            for (int j = 0; j < 10; j++) if (warp0) p[j] = s[(j >> 1) * 4 + 2 + (j & 1)];
            softmax_rows(p, q, pk, qk);
#pragma unroll
            for (int m = 0; m < 5; m++) { pa[2 * m] = !warp0 ? pk[m] : m == 0 ? qk[0] : m == 4 ? qk[1] : 0; pa[2 * m + 1] = pk[m]; }
            pa[10] = keep(0);
            pa[11] = keep(0);
        }
        {
            float o[64];
            ES(0, 4);
            mbar_wait_cl(bars + B_V * 8, par);
            fence_async_smem();
            wg_fence();
            wg_rs128<0>(o, &pa[0], mkdesc(E_VX, 2 * TG, 128, 0), 0);
            wg_rs128<0>(o, &pa[4], mkdesc(E_VX + 4 * TG, 2 * TG, 128, 0), 1);
            wg_rs128<0>(o, &pa[8], mkdesc(E_VM, 0, 128, 0), 1);
            wg_commit();
            nbar_arrive(NB_PVI, 256);
            float s0 = (bf_lo(pa[0]) + bf_hi(pa[0])) + (bf_lo(pa[8]) + bf_hi(pa[8])), s1 = 0.f;
#pragma unroll
            for (int m = 0; m < 5; m++) s1 += bf_lo(pa[2 * m + 1]) + bf_hi(pa[2 * m + 1]);
#pragma unroll
            for (int x = 1; x <= 2; x++) { s0 += __shfl_xor_sync(~0u, s0, x); s1 += __shfl_xor_sync(~0u, s1, x); }
            const float inv0 = rcp(warp0 ? s0 : s1), inv1 = rcp(s1);
            const int t = keep(tid);
            const uint32_t a = keep(sb + E_OM + rank * 2048 + (t >> 2) * 128 + (((t ^ (t >> 2)) & 3) << 4) + (t & 16) * 4);
            uint8_t* dst = g_o + ((i & (RING - 1)) * 64 + (blockIdx.x & ~1)) * 8192 + rank * 2048 + keep((t >> 2) * 64 + (((t ^ (t >> 3)) & 3) << 4));
            wg_wait<0>();
            ES(0, 6);
#define OW(j, h) pack2(o[4 * (j) + 2 * (h)] * ((h) ? inv1 : inv0), o[4 * (j) + 2 * (h) + 1] * ((h) ? inv1 : inv0))
#define OCHUNK(jj, h) make_uint4(OW(4 * (jj), h), OW(4 * (jj) + 1, h), OW(4 * (jj) + 2, h), OW(4 * (jj) + 3, h))
            if (warp0) {
#pragma unroll
                for (int jj = 0; jj < 4; jj++) {
                    const uint4 v = OCHUNK(jj, 1);
                    const uint32_t b = (a ^ ((jj & 1) * 64)) + (jj >> 1) * 1024;
                    st_async128(b + peer_off, v, bars + B_OM * 8 + peer_off);
                    sts128(b, v);
                }
                __syncwarp();
            }
            if (lane0) mbar_expect(bars + B_OM * 8, 2048 / 4);
            ES(0, 7);
            if (rank ? i >= LAG : i < NSEG) {
#pragma unroll
                for (int jj = 0; jj < 4; jj++) stg128(dst + jj * 4096, OCHUNK(jj, 0));
            }
#undef OCHUNK
#undef OW
            nbar_arrive(NB_WIB, NTHREADS);
        }
    }
    mbar_wait(bars + B_OM * 8, (NSTEP - 1) & 1);
}

__device__ __forceinline__ void engine_b(const Params& P, uint32_t sb) {
    const uint32_t bars = sb + E_BAR;
    uint32_t w[KRV][4];
    load_wregs<KRV, 1>(w, sb);
    const int rank = blockIdx.x & 1;
    const uint32_t peer_off = mapa(sb, rank ^ 1) - sb;
    const int tid = threadIdx.x & 127, warp = __shfl_sync(~0u, tid >> 5, 0);
    const bool lane0 = opaque(tid & 31) == 0;
    const uint32_t ax = opaque(sb + E_VX + tile_row<true>(tid, rank) + (tid & 3) * (2 * TG));
    const uint32_t am = opaque(sb + E_VM + tile_row<true>(tid, rank) + (tid & 3) * 4);
    const int kg = ((blockIdx.x & ~1) + tid) / 13;
    const uint32_t oflag = opaque(tid == 0 || (tid == 1 && kg * 13 == (blockIdx.x | 1)) ? (F_O + kg) * sizeof(g_flag[0]) : 0);
    const uint32_t e1 = lds32(sb + E_EPOCH) + 1;
    const uint8_t* img = g_xe;
    if (warp == 0) {
        x_ready(0, e1);
        fence_async_smem();
        if (elect()) { x_load(sb, img, 0); x_load(sb, img, 2); }
    }
#pragma unroll 1
    for (int i = 0; i < NSTEP; i++) {
        {
            const uint32_t xp = i & 1;
            float xv[32];
            uint64_t db = P.d128 + x_slot(0) / 16;
#define XB(c) x_wait(sb, c, xp); proj_x<KRV, false>(db, db, xv, xv, w, E_WV, c); wg_commit()
#pragma unroll
            for (int c = 0; c < GB1; c++) { XB(c); }
            if (i > 0) nbar_sync(NB_PVI, 256);
#pragma unroll
            for (int c = GB1; c < GB1 + GB2; c++) { XB(c); }
            ES(128, 14);
            if (warp == 0) {
                if (i > 0) mbar_wait(bars + B_OM * 8, xp ^ 1);
                if (elect()) { x_load(sb, img, 4); x_load(sb, img, 5); }
            }
            if (i > 0) nbar_sync(NB_WIB, NTHREADS);
#pragma unroll
            for (int c = GB1 + GB2; c < 4; c++) { XB(c); }
            wg_wait<0>();
            if (lane0) { mbar_arrive(bars + B_E01 * 8); mbar_arrive(bars + B_MF * 8); }
            if (oflag && i > 0) flag_signal((uint32_t*)((uint8_t*)g_flag[0][i - 1] + oflag));
            __syncwarp();
            if (warp == 1) {
                mbar_wait(bars + B_E01 * 8, xp);
                if (elect()) x_load(sb, img, 7);
            }
            ES(128, 28);
            XB(4); XB(5); XB(6);
            wg_wait<0>();
            if (lane0) { mbar_arrive_remote(bars + B_TF * 8 + peer_off); mbar_arrive(bars + B_TF * 8); }
            nbar_sync(NB_XI, 256);
            XB(7); XB(8);
#undef XB
            wg_wait<0>();
            if (lane0) mbar_arrive(bars + B_RF * 8);
            ES(128, 15);
            img += XIMG;
            if (warp == 0 && i < NSTEP - 1) x_ready(i + 1, e1);
            mbar_wait(bars + B_TF * 8, xp);
            nbar_sync(NB_MB, 256);
            if (warp == 0) {
                mbar_wait(bars + B_RF * 8, xp);
                if (elect()) {
#pragma unroll 1
                    for (int j = 0; j < 4; j++) {
                        const uint32_t o = sb + j * (2 * TG) + rank * 1024 + peer_off;
                        bulk_s2peer(o + E_KX, sb + E_OUT + j * SG, 1024, bars + B_QK * 8 + peer_off);
                        bulk_s2peer(o + E_QX, sb + E_OUT + (j + 4) * SG, 1024, bars + B_QK * 8 + peer_off);
                    }
                    if (i < NSTEP - 1) x_load(sb, img, 0);
                }
            }
            put_xv(xv, ax, rank, peer_off, bars + B_V * 8);
        }
        ES(128, 16);
        float d[8];
        nbar_sync(NB_QKI, NTHREADS);
        proj_mem<KRV, false>(P, d, w, E_WV);
        wg_wait<0>();
        put_mem<true>(d, am, rank, peer_off, bars + B_V * 8);
        __syncwarp();
        if (lane0) { mbar_expect(bars + B_V * 8, (1024 + 4096) / 4); mbar_arrive(bars + B_PD * 8); }
        ES(128, 18);
        nbar_sync(NB_SI, 256);
    }
    nbar_sync(NB_PVI, 256);
    nbar_sync(NB_WIB, NTHREADS);
    if (oflag) flag_signal((uint32_t*)((uint8_t*)g_flag[0][NSTEP - 1] + oflag));
}

__device__ __forceinline__ void engine_c(const Params& P, uint32_t sb) {
    const uint32_t bars = sb + E_BAR;
    const int e = blockIdx.x, rank = e & 1;
    const int tid = opaque(threadIdx.x & 127), lane = tid & 31, warp = __shfl_sync(~0u, tid >> 5, 0);
    if (warp == 0) {
        if (lane == 0) mbar_expect(bars + B_WL * 8, 2 * E_ST1 * 2048);
        __syncwarp();
        if (lane < E_ST1) {
            tma_w(sb + e_stage(lane), &P.tmWq, lane, e, bars + B_WL * 8);
            tma_w(sb + e_stage(E_ST1 + lane), &P.tmWv, lane, e, bars + B_WL * 8);
        }
        if (E_ST1 + lane < KRQ) tma_w_prefetch(&P.tmWq, E_ST1 + lane, e);
        if (E_ST1 + lane < KRV) tma_w_prefetch(&P.tmWv, E_ST1 + lane, e);
    } else if (warp == 1) {
        if (lane == 0) mbar_expect(bars + B_WS * 8, E_RING);
        __syncwarp();
        for (int ks = lane; ks < 36; ks += 32) tma_w(sb + E_WK + (m_pos(ks >> 2) * 4 + (ks & 3)) * 2048, &P.tmWk, ks, e, bars + B_WS * 8);
        if (lane < 36 - KRQ) tma_w(sb + E_WQ + lane * 2048, &P.tmWq, KRQ + lane, e, bars + B_WS * 8);
        if (lane < 36 - KRV) tma_w(sb + E_WV + lane * 2048, &P.tmWv, KRV + lane, e, bars + B_WS * 8);
        tma_w(sb + E_WO + lane * 2048, &P.tmWo, (e >> 1) * 8 + (lane & 7), rank * 4 + (lane >> 3), bars + B_WS * 8);
        if (lane < 4) tma_w(sb + E_WO + (32 + lane) * 2048, &P.tmWo, e * 4 + lane, 8, bars + B_WS * 8);
    }
    nbar_sync(NB_ALL, NTHREADS);
    if (warp == 0) {
        if (lane == 0) { fence_async_smem(); mbar_expect(bars + B_WL * 8, (KRQ + KRV - 2 * E_ST1) * 2048); }
        __syncwarp();
        if (E_ST1 + lane < KRQ) tma_w(sb + e_stage(lane), &P.tmWq, E_ST1 + lane, e, bars + B_WL * 8);
        if (E_ST1 + lane < KRV) tma_w(sb + e_stage(E_ST1 + lane), &P.tmWv, E_ST1 + lane, e, bars + B_WL * 8);
    }
    cluster_sync_all();
    mbar_wait(bars + B_WS * 8, 0);
    const uint32_t peer_off = mapa(sb, rank ^ 1) - sb;
    const uint32_t epoch = __shfl_sync(~0u, lds32(sb + E_EPOCH), 0);
    uint32_t ag_dst, w_init;
    {
        const bool nine = warp == 0 && (lane & 6) == 4;
        const int t = nine ? (lane & 1) * 2 + (lane >> 4) : lane & 3, f = (e >> 4) * 16 + ((e >> 1) & 7) + (lane & 8);
        const uint32_t row = (nine ? rank * 64 : (1 + 2 * warp + rank) * 128 + (lane >> 4) * 64) + f;
        ag_dst = opaque(row * 16 + t * 4 + (((row >> 3) & 3) == t) + (nine || !(lane & 4) ? 0 : 2));
        const uint16_t* m = (const uint16_t*)P.mem0 + (nine ? 8 : rank * 4 + warp) * 64 + f + t * (2 * DM);
        w_init = (uint32_t)__ldg(m) | ((uint32_t)__ldg(m + DM) << 16);
    }
    const uint32_t k_dst = opaque(sb + E_KM + tile_row<false>(tid, rank) + (tid & 3) * 4);
    const uint32_t mb = bars + (B_AG + warp) * 8, more = warp == 0 ? 2048 : 0;
    const bool lane0 = lane == 0;
    uint32_t rr = epoch * (NSTEP - 1) - 1, ra = epoch * NSTEP, ph = 0;
#pragma unroll 1
    for (int i = -1; i < NSTEP; i++, rr++, ra++) {
        const uint32_t par = i & 1;
        uint32_t w0 = w_init;
        if (i >= 0) {
            const uint32_t tag = ((rr >> 1) & 1) ^ 1;
            {
                float d[8];
                uint64_t da = P.d128 + E_WK / 16, db = P.dMem;
                wg_fence();
#pragma unroll
                for (int j = 0; j < 36; j++) {
                    if (j == QK_LEAD) nbar_arrive(NB_QKI, NTHREADS);
                    wg_ss16<1>(d, da, db, j > 0);
                    if (j < 35) { dmove(da, 128); dmove(db, (j & 3) < 3 ? 16 : 80); }
                }
                wg_commit();
                wg_wait<0>();
                put_mem<false>(d, k_dst, rank, peer_off, bars + B_QK * 8);
                __syncwarp();
                if (lane0) { mbar_arrive(bars + B_QK * 8); mbar_arrive(bars + B_PD * 8); }
                ES(256, 13);
                if (i == NSTEP - 1) break;
                if (warp == 3) {
                    mbar_wait(bars + B_PD * 8, par);
                    if (elect()) x_load(sb, g_xe + (i + 1) * XIMG, 2);
                    EFLUSH(i - 1);
                }
            }
            {
                float y[4][8];
                uint64_t db = P.dOm + rank * 64, da = P.d128 + (E_WO / 16 + 32 * 128);
                uint8_t* const dst = g_rs + (size_t)opaque(((rr & 1) * NENG + e) * 10240 + tid * 16);
#define W_TILE(Y, F) { _Pragma("unroll") for (int ks = 0; ks < 8; ks++) { wg_ss16<0>(y[Y], da, db, ks > 0 ? 1 : F); dmove(da, 128); dmove(db, ks == 7 ? -70 : ks == 3 ? 58 : 2); } wg_commit(); }
#define TAGGED(a, b) ((pack2(a, b) & ~1u) | tag)
#define W_ST(Y, T) { st_rlx128(dst + (T) * 2048, make_uint4(TAGGED(y[Y][0], y[Y][1]), pack2(y[Y][2], y[Y][3]), pack2(y[Y][4], y[Y][5]), pack2(y[Y][6], y[Y][7]))); __syncwarp(); }
                mbar_wait_cl(bars + B_OM * 8, par);
                fence_async_smem();
                ES(256, 19);
                wg_fence();
#pragma unroll
                for (int ks = 0; ks < 4; ks++) { wg_ss16<0>(y[0], da, db, ks > 0); dmove(da, ks < 3 ? 128 : -35 * 128); if (ks < 3) dmove(db, 2); }
                wg_commit();
                db = P.dOm;
                W_TILE(1, 0);
                W_TILE(2, 0);
                wg_wait<2>();
                st_rlx64(dst + 8192 - tid * 8, TAGGED(y[0][0], y[0][1]), pack2(y[0][2], y[0][3]));
                st_rlx64(dst + 9216 - tid * 8, TAGGED(y[0][4], y[0][5]), pack2(y[0][6], y[0][7]));
                __syncwarp();
                wg_fence();
                W_TILE(3, 0);
                wg_wait<2>(); W_ST(1, 0);
                wg_fence();
                W_TILE(0, -1);
                wg_wait<2>(); W_ST(2, 1);
                wg_wait<1>(); W_ST(3, 2);
                nbar_arrive(NB_WIA, 256);
                wg_wait<0>(); W_ST(0, 3);
                nbar_arrive(NB_WIB, NTHREADS);
#undef W_TILE
#undef W_ST
#undef TAGGED
            }
            ES(352, 20);
            spin_cycles(warp == 0 ? RS_DELAY0 : RS_DELAY - (3 - warp) * RS_SKEW);
            const uint32_t buf = sb + E_RS + (warp + 1) * 2048;
            const bool up = lane & 16, od = lane & 8;
            bool fetch = true;
            int n = 0;
#pragma unroll 1
            for (uint32_t u = more;;) {
                if (fetch) {
                    if (elect()) {
                        mbar_expect(mb, 2048 + more);
                        if (more) tma_2d(buf - 2048, &P.tmR9, 2048 + rank * 256 + (e >> 1) * 8, (rr & 1) * 64, mb);
                        tma_2d(buf, &P.tmRs, rank * 2560 + warp * 512 + (e >> 1) * 16, (rr & 1) * 32, mb);
                    }
                    mbar_wait(mb, ph);
                    ph ^= 1;
                }
                uint4 x[4];
#pragma unroll
                for (int j = 0; j < 4; j++) x[j] = lds128(buf - u + lane * 16 + j * 512);
                float a[8] = {bf_lo(x[0].x), bf_hi(x[0].x), bf_lo(x[0].y), bf_hi(x[0].y), bf_lo(x[0].z), bf_hi(x[0].z), bf_lo(x[0].w), bf_hi(x[0].w)};
#pragma unroll
                for (int j = 1; j < 4; j++) add8(a, x[j]);
#pragma unroll
                for (int k = 0; k < 4; k++) a[k] = (up ? a[4 + k] : a[k]) + __shfl_xor_sync(~0u, up ? a[k] : a[4 + k], 16);
                fetch = __any_sync(~0u, or_bit0(xor_or(x[0].x, x[1].x, tag), xor_or(x[2].x, x[3].x, tag)));
                if (fetch) { SPIN_CHECK(n, 1); continue; }
#pragma unroll
                for (int k = 0; k < 2; k++) a[k] = (od ? a[2 + k] : a[k]) + __shfl_xor_sync(~0u, od ? a[k] : a[2 + k], 8);
                a[0] += __shfl_xor_sync(~0u, a[0], 4); a[1] += __shfl_xor_sync(~0u, a[1], 4);
                if (u) { a[0] += __shfl_xor_sync(~0u, a[0], 2); a[1] += __shfl_xor_sync(~0u, a[1], 2); }
                if (u || !(lane & 4)) w0 = pack2(a[0], a[1]);
                if (!u) break;
                u = 0;
            }
            EV(352, 26, n); EV(256, 25, n); EV(320, 17, n);
            if (i == LAG - 1 && (ag_dst & 1024)) w0 = w_init;
        }
        const uint32_t atag = ((ra >> 1) & 1) ^ 1;
        uint8_t* const ag = g_ag + (ra & 1) * 18432;
        if (ag_dst & 1) w0 = (w0 & ~1u) | atag;
        if (!(ag_dst & 2)) st_rlx32(ag + (ag_dst & ~3u), w0);
        const uint32_t t0 = clock32(), off = 2048 + warp * 4096 - more;
        ES(352, 22); ES(256, 0);
        if (lane0) { mbar_arrive_remote(bars + B_TF * 8 + peer_off); mbar_arrive(bars + B_TF * 8); }
        const uint32_t chk = sb + E_MEM + 2048 + warp * 4096 + lane * 16 + (lane >> 3) * 4;
        mbar_wait(bars + B_MF * 8, par ^ 1);
        while ((int)(clock32() - t0) < AG_DELAY) {}
        int n = 0;
#pragma unroll 1
        while (true) {
            if (elect()) { mbar_expect(mb, 4096 + more); bulk_g2s(sb + E_MEM + off, ag + off, 4096 + more, mb); }
            mbar_wait(mb, ph);
            ph ^= 1;
            uint32_t v[12];
#pragma unroll
            for (int j = 0; j < 12; j++) v[j] = j < 8 || more ? lds32(chk + (j < 8 ? j : j - 12) * 512) : atag;
            if (!__any_sync(~0u, or_bit0(xor_or(v[0], v[1], atag) | xor_or(v[2], v[3], atag) | xor_or(v[4], v[5], atag),
                                         xor_or(v[6], v[7], atag) | xor_or(v[8], v[9], atag) | xor_or(v[10], v[11], atag)))) break;
            SPIN_CHECK(n, 2);
        }
        ES(352, 23); EV(352, 27, n); EV(256, 5, n);
        nbar_arrive(NB_MA, 256);
        nbar_arrive(NB_MB, 256);
        nbar_sync(NB_C, 128);
    }
    nbar_arrive(NB_WIB, NTHREADS);
    if (e == 0 && tid == 0) g_epoch = lds32(sb + E_EPOCH) + 1;
}

enum { ST_WO = 0, ST_F2 = 1, ST_F1 = 2 };
template <int ST> struct Stage;
template <> struct Stage<ST_WO> { static constexpr int NKS = 52, NR0 = 37, NR1 = 45, NT1 = 1, NSLOT = 8, TB = 0; };
template <> struct Stage<ST_F2> { static constexpr int NKS = 58, NR0 = 37, NR1 = 45, NT1 = 1, NSLOT = 5, TB = 1; };
template <> struct Stage<ST_F1> { static constexpr int NKS = 36, NR0 = 27, NR1 = 27, NT1 = 2, NSLOT = 5, TB = 0; };
template <int ST> struct StageMap : Stage<ST> {
    using S = Stage<ST>;
    static constexpr int NCH = (S::NKS + 3) / 4;
    static constexpr int W0A = 0, W0B = W0A + (S::NKS - S::NR0) * 2048, W1A = W0B + S::NKS * 2048, W1B = W1A + (S::NKS - S::NR1) * 2048;
    static constexpr int RNG = W1B + (S::NT1 - 1) * S::NKS * 2048;
    static_assert(RNG + S::NSLOT * 8192 <= SM_BAR && (S::NR0 + S::NR1) * 2048 <= SM_BAR, "stage smem");
};
__host__ __device__ constexpr int rs_idx(int ks, int nr, int nks) { return ks * nr / nks; }
__host__ __device__ constexpr bool is_rs(int ks, int nr, int nks) { return rs_idx(ks + 1, nr, nks) > rs_idx(ks, nr, nks); }

template <int ST, int SHAPE>
__device__ __forceinline__ void stage_consumer(const Params& P, uint32_t sb, int idx, const int WG) {
    using M = StageMap<ST>;
    constexpr int NR = SHAPE ? M::NR1 : M::NR0, NT = SHAPE ? M::NT1 : 2, NKS = M::NKS;
    const uint32_t bars = sb + SM_BAR;
    uint32_t w[NR][4];
    {
        const uint32_t base = frag_addr(sb + WG * (M::NR0 * 2048));
        mbar_wait(bars + B_WL * 8, 0);
#pragma unroll
        for (int r = 0; r < NR; r++) ldsm4t(w[r], base + r * 2048);
        nbar_sync(NB_ALL, 288);
        mbar_wait(bars + B_WS * 8, 0);
    }
    const bool shortk = ST != ST_F1 && idx >= 12;
    uint32_t s = 0, ph = 0;
#pragma unroll 1
    for (int j = 0; j < NSTEP; j++) {
        float d[NT][32];
        uint64_t da0 = P.d128 + WG * (M::W1A / 16), da1 = da0 + (NKS - NR) * 128;
        uint32_t prev = 0;
#pragma unroll
        for (int c = 0; c < M::NCH; c++) {
            if (c < M::NCH - 1 || !shortk) {
                mbar_wait(bars + (B_FULL + s) * 8, ph);
                if (c == 0) TS(WG * 128, j, WG * 4);
                uint64_t b = (ST == ST_WO ? P.d64 : P.d128) + (M::RNG / 16 + s * 512);
                wg_fence();
#pragma unroll
                for (int kk = 0; kk < 4; kk++) {
                    const int ks = c * 4 + kk;
                    if (ks < NKS) {
                        if (is_rs(ks, NR, NKS)) wg_rs64<M::TB>(d[0], w[rs_idx(ks, NR, NKS)], b, ks > 0);
                        else { wg_ss64<M::TB>(d[0], da0, b, ks > 0); dmove(da0, 128); }
                        if (NT > 1) { wg_ss64<M::TB>(d[NT - 1], da1, b, ks > 0); dmove(da1, 128); }
                        if (kk < 3) dmove(b, ST == ST_WO ? (kk == 1 ? 254 : 2) : M::TB ? 128 : 2);
                    }
                }
                wg_commit();
                if (c > 0) {
                    wg_wait<1>();
                    if ((fresh_tid() & 31) == 0) mbar_arrive(prev);
                }
                prev = bars + (B_EMPTY + s) * 8;
                if (++s == M::NSLOT) { s = 0; ph ^= 1; }
            }
        }
        const int tid = fresh_tid(), g = (tid >> 2) & 7, t = tid & 3, warp = (tid >> 5) & 3;
        wg_wait<0>();
        if ((tid & 31) == 0) mbar_arrive(prev);
        TS(WG * 128, j, WG * 4 + 1);
        if (ST == ST_F1) {
            uint8_t* dst = g_h + ((j & (RING - 1)) * FF + idx * 128 + WG * 64 + warp * 16 + g) * 128;
#pragma unroll
            for (int h = 0; h < 2; h++) {
#pragma unroll
                for (int c = 0; c < 2; c++) {
                    uint32_t pk[4];
#pragma unroll
                    for (int m = 0; m < 4; m++) {
                        const int o = 16 * c + 4 * m + 2 * h;
                        const float g0 = d[0][o], g1 = d[0][o + 1];
                        const float e0 = 1.f + ex2(fminf(-LOG2E * g0, 60.f)), e1 = 1.f + ex2(fminf(-LOG2E * g1, 60.f));
                        const float r = rcp(e0 * e1);
                        pk[m] = pack2(g0 * d[NT - 1][o] * (e1 * r), g1 * d[NT - 1][o + 1] * (e0 * r));
                    }
                    stg128(dst + h * 1024 + (((c * 4 + t) ^ g) << 4), make_uint4(pk[0], pk[1], pk[2], pk[3]));
                }
            }
            nbar_sync(NB_WG0 + WG, 128);
            TS(WG * 128, j, WG * 4 + 2);
            if ((tid & 127) == 0) {
                const int f0 = idx * 128 + WG * 64, k0 = f0 / 928, k1 = (f0 + 63) / 928;
                flag_signal(g_flag[F_H + k0][j]);
                if (k1 != k0) red_add_u32(g_flag[F_H + k1][j], 1);
            }
            __syncwarp();
            TS(WG * 128, j, WG * 4 + 3);
        } else {
            uint8_t* dst = g_part[ST & 1] + (((j & (RING - 1)) * 5 + idx / 3) * 64 + g) * 1152 + ((idx % 3) * 3 + WG) * 128 + warp * 32 + t * 8;
#pragma unroll
            for (int T = 0; T < NT; T++) {
#pragma unroll
                for (int m = 0; m < 8; m++)
                    stg64(dst + T * 256 + m * (8 * 1152), movm(pack2(d[T][4 * m], d[T][4 * m + 1])), movm(pack2(d[T][4 * m + 2], d[T][4 * m + 3])));
            }
            warp_arrive(bars + B_PUB * 8);
            TS(WG * 128, j, WG * 4 + 2);
        }
    }
}

template <int ST>
__device__ __forceinline__ void stage_producer(const Params& P, uint32_t sb, int idx) {
    using M = StageMap<ST>;
    const uint32_t bars = sb + SM_BAR;
    const int lane = threadIdx.x & 31;
    const int kg = ST == ST_F1 ? 0 : idx / 3;
    {
        const CUtensorMap* tm0 = ST == ST_WO ? &P.tmWo : ST == ST_F2 ? &P.tmW2 : &P.tmW1;
        const CUtensorMap* tm1 = ST == ST_F1 ? &P.tmW3 : tm0;
        const int k0 = kg * M::NKS, g0 = ST == ST_F1 ? idx * 2 : (idx % 3) * 3;
        if (ST != ST_WO) spin_cycles(G_DELAY);
        if (lane == 0) mbar_expect(bars + B_WL * 8, (M::NR0 + M::NR1) * 2048);
        __syncwarp();
#pragma unroll 1
        for (int ks = lane; ks < M::NKS; ks += 32) {
            if (is_rs(ks, M::NR0, M::NKS)) tma_w(sb + rs_idx(ks, M::NR0, M::NKS) * 2048, tm0, k0 + ks, g0, bars + B_WL * 8);
            else tma_w_prefetch(tm0, k0 + ks, g0);
            if (is_rs(ks, M::NR1, M::NKS)) tma_w(sb + (M::NR0 + rs_idx(ks, M::NR1, M::NKS)) * 2048, tm0, k0 + ks, g0 + 1, bars + B_WL * 8);
            else tma_w_prefetch(tm0, k0 + ks, g0 + 1);
            tma_w_prefetch(tm1, k0 + ks, ST == ST_F1 ? g0 : g0 + 2);
            if (ST == ST_F1) tma_w_prefetch(tm1, k0 + ks, g0 + 1);
        }
        nbar_sync(NB_ALL, 288);
        if (lane == 0) { fence_async_smem(); mbar_expect(bars + B_WS * 8, M::RNG); }
        __syncwarp();
#pragma unroll 1
        for (int ks = lane; ks < M::NKS; ks += 32) {
            if (!is_rs(ks, M::NR0, M::NKS)) tma_w(sb + M::W0A + (ks - rs_idx(ks, M::NR0, M::NKS)) * 2048, tm0, k0 + ks, g0, bars + B_WS * 8);
            if (!is_rs(ks, M::NR1, M::NKS)) tma_w(sb + M::W1A + (ks - rs_idx(ks, M::NR1, M::NKS)) * 2048, tm0, k0 + ks, g0 + 1, bars + B_WS * 8);
            tma_w(sb + M::W0B + ks * 2048, tm1, k0 + ks, ST == ST_F1 ? g0 : g0 + 2, bars + B_WS * 8);
            if (ST == ST_F1) tma_w(sb + M::W1B + ks * 2048, tm1, k0 + ks, g0 + 1, bars + B_WS * 8);
        }
    }
    if (lane != 0) return;
    const uint32_t e1 = lds32(sb + SM_EPOCH) + 1;
    const uint32_t target = e1 * (ST == ST_F1 ? 64 : ST == ST_WO ? (kg < 4 ? 14 : 12) : (kg < 4 ? 15 : 14));
    const int nch = M::NCH - (kg == 4);
    uint32_t s = 0, ph = 1;
#pragma unroll 1
    for (int j = 0; j < NSTEP; j++) {
        const int slot = j & (RING - 1);
        const uint8_t* src = ST == ST_F1 ? g_xf + slot * XIMG : ST == ST_WO ? g_o + (slot * 64 + kg * 13) * 8192 : g_h + (slot * FF + kg * 928) * 128;
        flag_poll(g_flag[ST == ST_F1 ? F_XF : (ST == ST_WO ? F_O : F_H) + kg][j], target);
        fence_acq_gpu();
        fence_async_glb();
        TS(256, j, 8);
#pragma unroll 1
        for (int c = 0; c < nch; c++) {
            const uint32_t bytes = (ST == ST_F2 && c == M::NCH - 1) ? 4096 : 8192;
            mbar_wait(bars + (B_EMPTY + s) * 8, ph);
            mbar_expect(bars + (B_FULL + s) * 8, bytes);
            bulk_g2s(sb + M::RNG + s * 8192, src + c * 8192, bytes, bars + (B_FULL + s) * 8);
            if (++s == M::NSLOT) { s = 0; ph ^= 1; }
        }
    }
}

template <int ST>
__device__ __forceinline__ void stage_split(const Params& P, uint32_t sb, int wg, int idx) {
    if (wg == 0) { reg_inc<240>(); stage_consumer<ST, 0>(P, sb, idx, 0); }
    else if (wg == 1) { reg_inc<240>(); stage_consumer<ST, 1>(P, sb, idx, 1); }
    else {
        reg_dec<24>();
        const int tid = fresh_tid();
        if (tid < 288) stage_producer<ST>(P, sb, idx);
        else if (tid == 288) {
#pragma unroll 1
            for (int j = 0; j < NSTEP; j++) {
                mbar_wait(sb + SM_BAR + B_PUB * 8, j & 1);
                flag_signal(g_flag[F_PW + ST][j]);
                TS(288, j, 9);
            }
        }
    }
}

#define NOG
__global__ void __cluster_dims__(2, 1, 1) __launch_bounds__(NTHREADS, 1) fused_kernel(const __grid_constant__ Params P) {
    extern __shared__ __align__(1024) uint8_t smem_raw[];
    const uint32_t sb = smem_u32(smem_raw);
    const int tid = threadIdx.x;
    const int wg = __shfl_sync(~0u, tid >> 7, 0);
    const int bid = blockIdx.x;
    if (tid == 0) {
        const uint32_t bars = sb + (bid < NENG ? E_BAR : SM_BAR);
        if ((sb & 0xffffff) != SM_BASE) __trap();
        TV(0, 126, 0, gtl()); TS(0, 126, 1);
        sts32(bars + 384, *(volatile uint32_t*)&g_epoch);
        for (int i = 0; i < 11; i++) mbar_init(bars + i * 8, 1);
        mbar_init(bars + B_QK * 8, 8); mbar_init(bars + B_V * 8, 4); mbar_init(bars + B_OM * 8, 4);
        mbar_init(bars + B_E01 * 8, 8); mbar_init(bars + B_TF * 8, 24);
        for (int i = 0; i < 8; i++) mbar_init(bars + (B_EMPTY + i) * 8, 8);
        mbar_init(bars + B_PUB * 8, 8);
        mbar_init(bars + B_RF * 8, 8); mbar_init(bars + B_PD * 8, 12); mbar_init(bars + B_MF * 8, 8);
        for (int i = 0; i < 4; i++) mbar_init(bars + (B_AG + i) * 8, 1);
        asm volatile("fence.mbarrier_init.release.cluster;" ::: "memory");
    }
    __syncthreads();
    if (bid < NENG) {
        if (wg == 0) { reg_inc<240>(); engine_a(P, sb); }
        else if (wg == 1) { reg_inc<200>(); engine_b(P, sb); }
        else { reg_dec<64>(); engine_c(P, sb); }
        TV(0, 126, 2, gtl()); TS(0, 126, 3);
        cluster_sync_all();
    } else if (bid < CTA_WO) {
        const int idx = bid - CTA_F1;
        if (wg < 2) { NOG; reg_inc<200>(); stage_consumer<ST_F1, 0>(P, sb, idx, wg); }
        else {
            reg_dec<104>();
            const int w = __shfl_sync(~0u, (fresh_tid() >> 5) & 3, 0);
            if (w == 0) {
NOG;
                stage_producer<ST_F1>(P, sb, idx);
            } else if (idx < 32) {
                ln_first(P, (w - 1) * 32 + idx, LN0_SPLIT, 96);
NOG;
                const uint32_t e1 = lds32(sb + SM_EPOCH) + 1;
                const int second = w == 3;
#pragma unroll 1
                for (int j = 0; j < (second ? NSEG : NSTEP); j++) {
                    if (w == 2 ? j >= LAG : j < NSEG) {
                        warp_wait(g_flag[F_PW + second][j], e1 * NWO);
                        TS(288, j, 10); TS(352, j, 13);
                        ln_row(P, 1 + second, j, (w == 2 ? 32 : 0) + idx);
                        TS(288, j, 11); TS(352, j, 14);
                    }
                    warp_signal(second ? g_flag[F_XE][j + LAG] : g_flag[F_XF][j]);
                    TS(288, j, 12); TS(352, j, 15);
                }
            }
        }
    } else if (bid < CTA_SP) {
NOG;
        if (bid < CTA_F2) stage_split<ST_WO>(P, sb, wg, bid - CTA_WO);
        else stage_split<ST_F2>(P, sb, wg, bid - CTA_F2);
    } else {
        const int w = (bid - CTA_SP) * 12 + (tid >> 5);
        ln_first(P, LN0_SPLIT + w, S_TOK, 24);
        const uint32_t e1 = lds32(sb + SM_EPOCH) + 1;
#pragma unroll 1
        for (int item = LAG * 32 + w; item < NSTEP * 32; item += 24) {
            warp_wait(g_flag[F_PF][item >> 5], e1 * NF2);
            ln_row(P, 3, item >> 5, 32 + (item & 31));
            __syncwarp();
            if ((tid & 31) == 0 && (item >> 5) + LAG + 1 < NSTEP) red_add_u32(g_flag[F_XE][(item >> 5) + LAG + 1], 1);
        }
        TV(0, 126, 2, gtl()); TS(0, 126, 3);
        if (w == 23) { if ((tid & 31) == 0) flag_poll(g_flag[F_DONE][0], e1 * (CTA_SP * 12)); }
        return;
    }
    __syncwarp();
    if ((fresh_tid() & 31) == 0) red_add_u32(g_flag[F_DONE][0], 1);
}

typedef CUresult (*EncodeFn)(CUtensorMap*, CUtensorMapDataType, cuuint32_t, void*, const cuuint64_t*, const cuuint64_t*,
                             const cuuint32_t*, const cuuint32_t*, CUtensorMapInterleave, CUtensorMapSwizzle,
                             CUtensorMapL2promotion, CUtensorMapFloatOOBfill);

void make_map(EncodeFn enc, CUtensorMap* m, const void* p, int rows, int cols) {
    cuuint64_t dims[3] = {64, (cuuint64_t)rows, (cuuint64_t)(cols / 64)};
    cuuint64_t strides[2] = {(cuuint64_t)cols * 2, 128};
    cuuint32_t box[3] = {64, 16, 1};
    cuuint32_t es[3] = {1, 1, 1};
    enc(m, CU_TENSOR_MAP_DATA_TYPE_BFLOAT16, 3, (void*)p, dims, strides, box, es, CU_TENSOR_MAP_INTERLEAVE_NONE,
        CU_TENSOR_MAP_SWIZZLE_128B, CU_TENSOR_MAP_L2_PROMOTION_L2_128B, CU_TENSOR_MAP_FLOAT_OOB_FILL_NONE);
}

void make_map2(EncodeFn enc, CUtensorMap* m, void* p, int words, int rows, int bw, int br) {
    cuuint64_t dims[2] = {(cuuint64_t)words, (cuuint64_t)rows};
    cuuint64_t strides[1] = {(cuuint64_t)words * 4};
    cuuint32_t box[2] = {(cuuint32_t)bw, (cuuint32_t)br};
    cuuint32_t es[2] = {1, 1};
    enc(m, CU_TENSOR_MAP_DATA_TYPE_UINT32, 2, p, dims, strides, box, es, CU_TENSOR_MAP_INTERLEAVE_NONE,
        CU_TENSOR_MAP_SWIZZLE_NONE, CU_TENSOR_MAP_L2_PROMOTION_NONE, CU_TENSOR_MAP_FLOAT_OOB_FILL_NONE);
}

}

extern "C" void kernel_launch(void* const* d_in, const int* in_sizes, int n_in, void* d_out, int out_size) {
    (void)in_sizes; (void)n_in; (void)out_size;
    static EncodeFn enc = nullptr;
    static void* rs = nullptr;
    if (!enc) {
        void* fn = nullptr;
        cudaDriverEntryPointQueryResult qr;
        cudaGetDriverEntryPoint("cuTensorMapEncodeTiled", &fn, cudaEnableDefault, &qr);
        enc = (EncodeFn)fn;
        cudaGetSymbolAddress(&rs, g_rs);
        cudaFuncSetAttribute(fused_kernel, cudaFuncAttributeMaxDynamicSharedMemorySize, SM_TOTAL);
    }
    Params P;
    make_map(enc, &P.tmWq, d_in[2], DM, 4096);
    make_map(enc, &P.tmWk, d_in[3], DM, 4096);
    make_map(enc, &P.tmWv, d_in[4], DM, 4096);
    make_map(enc, &P.tmWo, d_in[5], 4096, DM);
    make_map(enc, &P.tmW1, d_in[8], DM, FF);
    make_map(enc, &P.tmW3, d_in[9], DM, FF);
    make_map(enc, &P.tmW2, d_in[10], FF, DM);
    make_map2(enc, &P.tmRs, rs, 5120, 64, 16, 32);
    make_map2(enc, &P.tmR9, rs, 2560, 128, 8, 64);
    P.d128 = mkdesc(0, 1024, 1024, 1);
    P.d64 = mkdesc(0, 16, 512, 2);
    P.dMem = mkdesc(E_MEM, 128, 1024, 0);
    P.dOm = mkdesc(E_OM, 16, 2048, 1);
    P.dQ = mkdesc(E_QX, 128, TG, 0);
    P.dK = mkdesc(E_KX, 128, 2 * TG, 0);
    P.x = (const bf16*)d_in[0];
    P.mem0 = (const bf16*)d_in[1];
    P.out = (bf16*)d_out;
    fused_kernel<<<NGRID, NTHREADS, SM_TOTAL>>>(P);
}
```

```cpp
#include <cuda_runtime.h>
#include <cuda_bf16.h>
#include <cuda.h>
#include <stdint.h>

typedef __nv_bfloat16 bf16;

namespace {

constexpr int S_TOK = 2048, DM = 576, NH = 32, FF = 4608, NSEG = 64;
#define LAG 7
#define RING 8
static_assert(RING > LAG && (RING & (RING - 1)) == 0, "ring slots are only protected by the dataflow cycle");
constexpr int NSTEP = NSEG + LAG;
constexpr int NROUND = NSTEP + 1;
constexpr int NENG = 64, NF1 = 36, NWO = 15, NF2 = 15, NGRID = 132;
constexpr int CTA_F1 = NENG, CTA_WO = CTA_F1 + NF1, CTA_F2 = CTA_WO + NWO, CTA_SP = CTA_F2 + NF2;
constexpr int NTHREADS = 384;
constexpr int XIMG = 9 * 8192;
constexpr int LN0_SPLIT = 1088;
#define RS_DELAY 550
#define RS_SKEW 60
#define RS_DELAY0 0
#define AG_DELAY 300
#define QK_LEAD 33
#define GB1 2
#define GB2 (4 - GB1)
#define GB3 3
#define LATE_WAIT 900
#define LATE_MUL 7
#define X7_DELAY 0
#define AG_GAP 0
#define F1_NR 29
#define F1_SLOTS 4
#define G_DELAY 9000
constexpr int SPIN_LIMIT = 4000000;

enum { F_XE = 0, F_XF, F_PW, F_PF, F_O, F_H = F_O + 5, F_DONE = F_H + 5, F_COUNT };
__device__ uint32_t g_flag[F_COUNT][NSTEP + 2][8];
__device__ uint32_t g_epoch;
__device__ unsigned long long g_latest;
__device__ __align__(1024) uint8_t g_xe[NSTEP * XIMG];
__device__ __align__(1024) uint8_t g_xf[RING * XIMG];
__device__ __align__(1024) uint8_t g_o[RING * 64 * 8192];
__device__ __align__(1024) uint8_t g_h[RING * FF * 128];
__device__ __align__(1024) uint8_t g_part[2][RING * 64 * 5 * 1152];
__device__ __align__(1024) uint8_t g_x1[RING * 64 * 1152];
__device__ __align__(1024) uint8_t g_res[2][S_TOK * 1152];
__device__ __align__(1024) uint8_t g_rs[2 * NENG * 10240];
__device__ __align__(1024) uint8_t g_ag[2 * 18432];

struct Params {
    CUtensorMap tmWq, tmWk, tmWv, tmWo, tmW1, tmW3, tmW2, tmRs, tmR9;
    uint64_t d128, d64, dOm, dQ, dK, dX[4], dXk, dMq, dMk, dMv, dWk, dWo;
    uint32_t zero;
    const bf16* x;
    const bf16* mem0;
    bf16* out;
};

constexpr int SM_TOTAL = 232448;
constexpr int SM_BAR = SM_TOTAL - 512;
constexpr int KRQ = 34, KRV = 35;
constexpr int E_WK = 0;
constexpr int E_WO = E_WK + 36 * 2048;
constexpr int E_WQ = E_WO + 36 * 2048;
constexpr int E_WV = E_WQ + (36 - KRQ) * 2048;
constexpr int E_RING = E_WV + (36 - KRV) * 2048;
constexpr int E_MEM = E_RING + 2 * 8192;
constexpr int E_OM = E_MEM + 18432;
constexpr int TG = 2064;
constexpr int E_T = E_OM + 4096;
constexpr int E_QX = E_T, E_QM = E_T + TG, E_KX = E_T + 3 * TG, E_KM = E_T + 11 * TG, E_VX = E_T + 8 * TG, E_VM = E_T + 13 * TG;
constexpr int E_RS = E_T + 16384;
constexpr int E_BAR = E_T + 15 * TG;
constexpr int E_R2 = SM_TOTAL - 8192;
constexpr int SG = 1056, E_OUT = SM_TOTAL - 7 * SG - 1024;
static_assert(E_BAR + 512 <= E_OUT && E_RING % 1024 == 0 && E_MEM % 1024 == 0 && E_OM % 1024 == 0 && E_T % 1024 == 0 && E_R2 % 1024 == 0, "engine smem");
constexpr int E_ST1 = 19;
__host__ __device__ constexpr int e_stage(int j) { return j < 34 ? E_RING + j * 2048 : E_R2 + (j - 34) * 2048; }
static_assert(E_RING + 34 * 2048 <= E_BAR && 2 * E_ST1 <= 38, "staging");
__host__ __device__ constexpr int x_slot(int c) {
    return c < 2 ? E_RING + c * 8192 : c < 4 ? E_MEM + (c - 2) * 8192 : c == 4 ? E_R2 : c < 7 ? E_T + (c - 5) * 8192 : E_RING + (c - 7) * 8192;
}
enum { B_XF = 0, B_WL = 9, B_WS, B_QK, B_V, B_OM, B_E01, B_TF, B_RF = 1, B_PD = 3, B_MF = 6, B_M = 8, B_R9 = 49, B_RS = B_R9 + 2, B_AG = B_RS + 4, B_FULL = 0, B_EMPTY = 16, B_PUB = 32 };
enum { NB_ALL = 1, NB_MA, NB_QKI, NB_SI, NB_PVI, NB_WIA, NB_WIB, NB_XI, NB_C, NB_WG0, NB_WG1 };
constexpr int SM_EPOCH = SM_BAR + 384, E_EPOCH = E_BAR + 384, E_SEL = E_BAR + 504;

#define SPIN_CHECK(n, code) asm volatile("{.reg .pred p; setp.gt.s32 p, %0, %1; @p st.global.u32 [%2], %0;}" :: "r"(++(n)), "n"(SPIN_LIMIT), "l"(0ull))

#define EV(thr, k, v)
#define ES(thr, k)
#define EFLUSH(step)
#define TS(thr, step, k)
#define TV(thr, step, k, v)

__device__ __forceinline__ uint32_t smem_u32(const void* p) { return (uint32_t)__cvta_generic_to_shared(p); }
__device__ __forceinline__ uint32_t mapa(uint32_t a, uint32_t r) {
    uint32_t o; asm("mapa.shared::cluster.u32 %0, %1, %2;" : "=r"(o) : "r"(a), "r"(r)); return o;
}
__device__ __forceinline__ void mbar_init(uint32_t b, uint32_t cnt) {
    asm volatile("mbarrier.init.shared::cta.b64 [%0], %1;" :: "r"(b), "r"(cnt) : "memory");
}
__device__ __forceinline__ void mbar_arrive(uint32_t b) {
    asm volatile("mbarrier.arrive.shared::cta.b64 _, [%0];" :: "r"(b) : "memory");
}
__device__ __forceinline__ void mbar_arrive_remote(uint32_t b) {
    asm volatile("mbarrier.arrive.relaxed.cluster.shared::cluster.b64 _, [%0];" :: "r"(b) : "memory");
}
__device__ __forceinline__ void mbar_expect(uint32_t b, uint32_t bytes) {
    asm volatile("mbarrier.arrive.expect_tx.shared::cta.b64 _, [%0], %1;" :: "r"(b), "r"(bytes) : "memory");
}
#define MBAR_WAIT(SEM) asm volatile("{.reg .pred p; W: mbarrier.try_wait.parity" SEM ".shared::cta.b64 p, [%0], %1; @!p bra W;}" :: "r"(b), "r"(par) : "memory")
__device__ __forceinline__ void mbar_wait(uint32_t b, uint32_t par) { MBAR_WAIT(""); }
__device__ __forceinline__ void mbar_wait_cl(uint32_t b, uint32_t par) {
    MBAR_WAIT(".relaxed.cluster");
    asm volatile("fence.acquire.sync_restrict::shared::cluster.cluster;" ::: "memory");
}
__device__ __forceinline__ void nbar_sync(int id, int n) { asm volatile("bar.sync %0, %1;" :: "r"(id), "r"(n) : "memory"); }
__device__ __forceinline__ void nbar_arrive(int id, int n) { asm volatile("bar.arrive %0, %1;" :: "r"(id), "r"(n) : "memory"); }
__device__ __forceinline__ uint32_t nbar_any(int id, int n, uint32_t v) {
    uint32_t r;
    asm volatile("{.reg .pred p, q; setp.ne.u32 p, %3, 0; bar.red.or.pred q, %1, %2, p; selp.u32 %0, 1, 0, q;}" : "=r"(r) : "r"(id), "r"(n), "r"(v) : "memory");
    return r;
}
__device__ __forceinline__ uint32_t clock_after(uint32_t zero) {
    uint32_t t;
    asm volatile("{.reg .pred p; setp.eq.u32 p, %1, 0; mov.u32 %0, 0; @p mov.u32 %0, %%clock;}" : "=r"(t) : "r"(zero) : "memory");
    return t;
}
__device__ __forceinline__ void cluster_sync_all() {
    asm volatile("barrier.cluster.arrive.release.aligned; barrier.cluster.wait.acquire.aligned;" ::: "memory");
}
__device__ __forceinline__ void fence_async_smem() { asm volatile("fence.proxy.async.shared::cta;" ::: "memory"); }
__device__ __forceinline__ void fence_async_glb() { asm volatile("fence.proxy.async.global;" ::: "memory"); }
__device__ __forceinline__ void fence_rel_gpu() { asm volatile("fence.release.gpu;" ::: "memory"); }
__device__ __forceinline__ void fence_acq_gpu() { asm volatile("fence.acquire.gpu;" ::: "memory"); }
__device__ __forceinline__ int fresh_tid() { int t; asm volatile("mov.u32 %0, %%tid.x;" : "=r"(t)); return t; }
__device__ __forceinline__ int fresh_bid() { int t; asm volatile("mov.u32 %0, %%ctaid.x;" : "=r"(t)); return t; }
__device__ __forceinline__ uint32_t keep(uint32_t v) { asm volatile("" : "+r"(v)); return v; }
__device__ __forceinline__ uint32_t opaque(uint32_t v) { return __shfl_xor_sync(~0u, v, 0); }
__device__ __forceinline__ bool elect() {
    uint32_t p; asm volatile("{.reg .pred p; elect.sync _|p, 0xffffffff; selp.u32 %0, 1, 0, p;}" : "=r"(p)); return p;
}
__device__ __forceinline__ uint32_t clock32() { uint32_t t; asm volatile("mov.u32 %0, %%clock;" : "=r"(t) :: "memory"); return t; }
__device__ __forceinline__ void red_add_u32(uint32_t* p, uint32_t v) {
    asm volatile("red.relaxed.gpu.global.add.u32 [%0], %1;" :: "l"(p), "r"(v) : "memory");
}
__device__ __forceinline__ uint32_t ld_rlx(const uint32_t* p) {
    uint32_t v; asm volatile("ld.relaxed.gpu.global.u32 %0, [%1];" : "=r"(v) : "l"(p) : "memory"); return v;
}
__device__ __forceinline__ void st_rlx128(void* p, uint4 v) {
    asm volatile("{.reg .b128 r; .reg .b64 a, b; mov.b64 a, {%1,%2}; mov.b64 b, {%3,%4}; mov.b128 r, {a, b}; st.relaxed.gpu.global.b128 [%0], r;}"
                 :: "l"(p), "r"(v.x), "r"(v.y), "r"(v.z), "r"(v.w) : "memory");
}
__device__ __forceinline__ void st_rlx64(void* p, uint32_t a, uint32_t b) {
    asm volatile("{.reg .b64 r; mov.b64 r, {%1,%2}; st.relaxed.gpu.global.b64 [%0], r;}" :: "l"(p), "r"(a), "r"(b) : "memory");
}
__device__ __forceinline__ void st_rlx32(void* p, uint32_t v) { asm volatile("st.relaxed.gpu.global.u32 [%0], %1;" :: "l"(p), "r"(v) : "memory"); }
__device__ __forceinline__ uint32_t xor_or(uint32_t a, uint32_t b, uint32_t t) {
    uint32_t d; asm("lop3.b32 %0, %1, %2, %3, 0x7E;" : "=r"(d) : "r"(a), "r"(b), "r"(t)); return d;
}
__device__ __forceinline__ uint32_t tagged(uint32_t w, uint32_t m, uint32_t tag) {
    uint32_t d; asm("lop3.b32 %0, %1, %2, %3, 0xB8;" : "=r"(d) : "r"(w), "r"(m), "r"(tag)); return d;
}
__device__ __forceinline__ uint32_t or3(uint32_t a, uint32_t b, uint32_t c) {
    uint32_t d; asm("lop3.b32 %0, %1, %2, %3, 0xFE;" : "=r"(d) : "r"(a), "r"(b), "r"(c)); return d;
}
__device__ __forceinline__ uint32_t or_bit0(uint32_t a, uint32_t b) {
    uint32_t d; asm("lop3.b32 %0, %1, %2, 1, 0xA8;" : "=r"(d) : "r"(a), "r"(b)); return d;
}
__device__ __forceinline__ uint4 ld_l2_128(const void* p) {
    uint4 v;
    asm volatile("ld.relaxed.gpu.global.v4.u32 {%0,%1,%2,%3}, [%4];" : "=r"(v.x), "=r"(v.y), "=r"(v.z), "=r"(v.w) : "l"(p) : "memory");
    return v;
}
__device__ __forceinline__ void stg128(void* p, uint4 v) {
    asm volatile("st.global.v4.b32 [%0], {%1,%2,%3,%4};" :: "l"(p), "r"(v.x), "r"(v.y), "r"(v.z), "r"(v.w) : "memory");
}
__device__ __forceinline__ void stg64(void* p, uint32_t a, uint32_t b) {
    asm volatile("st.global.v2.b32 [%0], {%1,%2};" :: "l"(p), "r"(a), "r"(b) : "memory");
}
__device__ __forceinline__ void st_async128(uint32_t a, uint4 v, uint32_t mb) {
    asm volatile("st.async.shared::cluster.mbarrier::complete_tx::bytes.v4.b32 [%0], {%1,%2,%3,%4}, [%5];"
                 :: "r"(a), "r"(v.x), "r"(v.y), "r"(v.z), "r"(v.w), "r"(mb) : "memory");
}
__device__ __forceinline__ void st_async32(uint32_t a, uint32_t v, uint32_t mb) {
    asm volatile("st.async.shared::cluster.mbarrier::complete_tx::bytes.b32 [%0], %1, [%2];" :: "r"(a), "r"(v), "r"(mb) : "memory");
}
__device__ __forceinline__ void sts128(uint32_t a, uint4 v) {
    asm volatile("st.shared.v4.b32 [%0], {%1,%2,%3,%4};" :: "r"(a), "r"(v.x), "r"(v.y), "r"(v.z), "r"(v.w) : "memory");
}
__device__ __forceinline__ void sts32(uint32_t a, uint32_t v) { asm volatile("st.shared.b32 [%0], %1;" :: "r"(a), "r"(v) : "memory"); }
__device__ __forceinline__ uint32_t lds32(uint32_t a) { uint32_t v; asm volatile("ld.shared.b32 %0, [%1];" : "=r"(v) : "r"(a) : "memory"); return v; }
__device__ __forceinline__ uint2 lds64(uint32_t a) {
    uint2 v; asm volatile("ld.shared.v2.b32 {%0,%1}, [%2];" : "=r"(v.x), "=r"(v.y) : "r"(a) : "memory"); return v;
}
__device__ __forceinline__ uint4 lds128(uint32_t a) {
    uint4 v; asm volatile("ld.shared.v4.b32 {%0,%1,%2,%3}, [%4];" : "=r"(v.x), "=r"(v.y), "=r"(v.z), "=r"(v.w) : "r"(a) : "memory"); return v;
}
__device__ __forceinline__ void bulk_g2s(uint32_t dst, const void* src, uint32_t bytes, uint32_t mb) {
    asm volatile("cp.async.bulk.shared::cluster.global.mbarrier::complete_tx::bytes [%0], [%1], %2, [%3];"
                 :: "r"(dst), "l"(src), "r"(bytes), "r"(mb) : "memory");
}
__device__ __forceinline__ void bulk_s2peer(uint32_t dst, uint32_t src, uint32_t bytes, uint32_t mb) {
    asm volatile("cp.async.bulk.shared::cluster.shared::cta.mbarrier::complete_tx::bytes [%0], [%1], %2, [%3];"
                 :: "r"(dst), "r"(src), "r"(bytes), "r"(mb) : "memory");
}
__device__ __forceinline__ void tma_2d(uint32_t dst, const CUtensorMap* tm, int x, int y, uint32_t mb) {
    asm volatile("cp.async.bulk.tensor.2d.shared::cluster.global.mbarrier::complete_tx::bytes [%0], [%1, {%2,%3}], [%4];"
                 :: "r"(dst), "l"(tm), "r"(x), "r"(y), "r"(mb) : "memory");
}
__device__ __forceinline__ void tma_w(uint32_t dst, const CUtensorMap* tm, int ks, int grp, uint32_t mb) {
    asm volatile("cp.async.bulk.tensor.3d.shared::cluster.global.mbarrier::complete_tx::bytes [%0], [%1, {%2,%3,%4}], [%5];"
                 :: "r"(dst), "l"(tm), "r"(0), "r"(ks * 16), "r"(grp), "r"(mb) : "memory");
}
__device__ __forceinline__ void tma_w_prefetch(const CUtensorMap* tm, int ks, int grp) {
    asm volatile("cp.async.bulk.prefetch.tensor.3d.L2.global [%0, {%1,%2,%3}];" :: "l"(tm), "r"(0), "r"(ks * 16), "r"(grp) : "memory");
}
__device__ __forceinline__ void ldsm4t(uint32_t* r, uint32_t a) {
    asm volatile("ldmatrix.sync.aligned.m8n8.x4.trans.shared.b16 {%0,%1,%2,%3}, [%4];"
                 : "=r"(r[0]), "=r"(r[1]), "=r"(r[2]), "=r"(r[3]) : "r"(a) : "memory");
}
__device__ __forceinline__ uint32_t movm(uint32_t a) {
    uint32_t d; asm volatile("movmatrix.sync.aligned.m8n8.trans.b16 %0, %1;" : "=r"(d) : "r"(a)); return d;
}
__device__ __forceinline__ uint32_t pack2(float lo, float hi) {
    uint32_t d; asm("cvt.rn.bf16x2.f32 %0, %1, %2;" : "=r"(d) : "f"(hi), "f"(lo)); return d;
}
__device__ __forceinline__ float bf_lo(uint32_t w) { return __uint_as_float(w << 16); }
__device__ __forceinline__ float bf_hi(uint32_t w) { return __uint_as_float(w & 0xffff0000u); }
__device__ __forceinline__ float ex2(float x) { float y; asm("ex2.approx.ftz.f32 %0, %1;" : "=f"(y) : "f"(x)); return y; }
__device__ __forceinline__ float rcp(float x) { float y; asm("rcp.approx.ftz.f32 %0, %1;" : "=f"(y) : "f"(x)); return y; }
__device__ __forceinline__ void spin_cycles(int c) {
    uint32_t t0, t1;
    asm volatile("mov.u32 %0, %%clock;" : "=r"(t0));
    do { asm volatile("mov.u32 %0, %%clock;" : "=r"(t1)); } while ((int)(t1 - t0) < c);
}
template <int N> __device__ __forceinline__ void reg_inc() { asm volatile("setmaxnreg.inc.sync.aligned.u32 %0;" :: "n"(N)); }
template <int N> __device__ __forceinline__ void reg_dec() { asm volatile("setmaxnreg.dec.sync.aligned.u32 %0;" :: "n"(N)); }

__device__ __forceinline__ void flag_poll(const uint32_t* f, uint32_t target) {
    int n = 0;
    while ((int)(ld_rlx(f) - target) < 0) {
        SPIN_CHECK(n, (int)(f - &g_flag[0][0][0]) / 8);
    }
}
__device__ __forceinline__ void flag_signal_after(const Params& P, uint32_t* f, uint32_t loaded) { red_add_u32(f, (loaded & P.zero) + 1); }
__device__ __forceinline__ void flag_signal(uint32_t* f) {
    fence_rel_gpu();
    red_add_u32(f, 1);
}

constexpr uint32_t SM_BASE = 1024;
__host__ __device__ constexpr uint64_t mkdesc(uint32_t off, uint32_t lbo, uint32_t sbo, uint32_t swz) {
    return (uint64_t)((SM_BASE + off) >> 4) | ((uint64_t)(lbo >> 4) << 16) | ((uint64_t)(sbo >> 4) << 32) | ((uint64_t)swz << 62);
}
__device__ __forceinline__ void dmove(uint64_t& d, int delta) { asm volatile("add.s64 %0, %0, %1;" : "+l"(d) : "l"((long long)delta)); }
__device__ __forceinline__ void wg_fence() { asm volatile("wgmma.fence.sync.aligned;" ::: "memory"); }
__device__ __forceinline__ void wg_commit() { asm volatile("wgmma.commit_group.sync.aligned;" ::: "memory"); }
template <int N> __device__ __forceinline__ void wg_wait() { asm volatile("wgmma.wait_group.sync.aligned %0;" :: "n"(N) : "memory"); }

#define F4(c, d, o) c(d[o]), c(d[o + 1]), c(d[o + 2]), c(d[o + 3])
#define F8(c, d, o) F4(c, d, o), F4(c, d, o + 4)
#define F32(c, d, o) F8(c, d, o), F8(c, d, o + 8), F8(c, d, o + 16), F8(c, d, o + 24)
#define L8 "%0,%1,%2,%3,%4,%5,%6,%7"
#define L20 L8 ",%8,%9,%10,%11,%12,%13,%14,%15,%16,%17,%18,%19"
#define L32 L20 ",%20,%21,%22,%23,%24,%25,%26,%27,%28,%29,%30,%31"
#define L64 L32 ",%32,%33,%34,%35,%36,%37,%38,%39,%40,%41,%42,%43,%44,%45,%46,%47,%48,%49,%50,%51,%52,%53,%54,%55,%56,%57,%58,%59,%60,%61,%62,%63"
#define O8(c) F8(c, d, 0)
#define O20(c) F8(c, d, 0), F8(c, d, 8), F4(c, d, 16)
#define O32(c) F32(c, d, 0)
#define O64(c) F32(c, d, 0), F32(c, d, 32)
#define WG_BOTH(TXT_PRE, TXT_POST, OUTS, ...)                                                   \
    if (acc > 0) asm volatile(TXT_PRE "1" TXT_POST : OUTS("+f") : __VA_ARGS__);                 \
    else if (acc < 0) asm volatile(TXT_PRE "0" TXT_POST : OUTS("+f") : __VA_ARGS__);            \
    else asm volatile(TXT_PRE "0" TXT_POST : OUTS("=f") : __VA_ARGS__)
#define AREGS "r"(a[0]), "r"(a[1]), "r"(a[2]), "r"(a[3])
template <int TB> __device__ __forceinline__ void wg_rs16(float* d, const uint32_t* a, uint64_t db, int acc) {
    WG_BOTH("wgmma.mma_async.sync.aligned.m64n16k16.f32.bf16.bf16 {" L8 "}, {%8,%9,%10,%11}, %12, ", ", 1, 1, %13;", O8, AREGS, "l"(db), "n"(TB));
}
template <int TB> __device__ __forceinline__ void wg_ss16(float* d, uint64_t da, uint64_t db, int acc) {
    WG_BOTH("wgmma.mma_async.sync.aligned.m64n16k16.f32.bf16.bf16 {" L8 "}, %8, %9, ", ", 1, 1, 1, %10;", O8, "l"(da), "l"(db), "n"(TB));
}
template <int TB> __device__ __forceinline__ void wg_ss40(float* d, uint64_t da, uint64_t db, int acc) {
    WG_BOTH("wgmma.mma_async.sync.aligned.m64n40k16.f32.bf16.bf16 {" L20 "}, %20, %21, ", ", 1, 1, 1, %22;", O20, "l"(da), "l"(db), "n"(TB));
}
template <int TB> __device__ __forceinline__ void wg_rs64(float* d, const uint32_t* a, uint64_t db, int acc) {
    WG_BOTH("wgmma.mma_async.sync.aligned.m64n64k16.f32.bf16.bf16 {" L32 "}, {%32,%33,%34,%35}, %36, ", ", 1, 1, %37;", O32, AREGS, "l"(db), "n"(TB));
}
template <int TB> __device__ __forceinline__ void wg_ss64(float* d, uint64_t da, uint64_t db, int acc) {
    WG_BOTH("wgmma.mma_async.sync.aligned.m64n64k16.f32.bf16.bf16 {" L32 "}, %32, %33, ", ", 1, 1, 1, %34;", O32, "l"(da), "l"(db), "n"(TB));
}
template <int TB> __device__ __forceinline__ void wg_rs128(float* d, const uint32_t* a, uint64_t db, int acc) {
    WG_BOTH("wgmma.mma_async.sync.aligned.m64n128k16.f32.bf16.bf16 {" L64 "}, {%64,%65,%66,%67}, %68, ", ", 1, 1, %69;", O64, AREGS, "l"(db), "n"(TB));
}
__device__ __forceinline__ uint32_t frag_addr(uint32_t base) {
    const int tid = threadIdx.x, i = tid & 7, j = (tid >> 3) & 3, warp = (tid >> 5) & 3;
    return base + ((j >> 1) * 8 + i) * 128 + ((((warp << 1) + (j & 1)) ^ i) << 4);
}

constexpr float SM_SCALE = 0.08838834764831845f;
constexpr float LOG2E = 1.4426950408889634f;

__device__ __forceinline__ void add8(float* f, uint4 a) {
    f[0] += bf_lo(a.x); f[1] += bf_hi(a.x); f[2] += bf_lo(a.y); f[3] += bf_hi(a.y);
    f[4] += bf_lo(a.z); f[5] += bf_hi(a.z); f[6] += bf_lo(a.w); f[7] += bf_hi(a.w);
}
__device__ __forceinline__ void sum_row(uint4* xw, const uint8_t* part, const uint8_t* res, uint32_t tag, uint32_t buf, uint32_t mb, uint32_t& ph, int l) {
    int n = 0;
#pragma unroll 1
    while (true) {
        if (elect()) { mbar_expect(mb, 6 * 1152); bulk_g2s(buf, part, 5 * 1152, mb); bulk_g2s(buf + 5 * 1152, res, 1152, mb); }
        SPIN_CHECK(n, 7);
        mbar_wait(mb, ph);
        ph ^= 1;
        uint32_t bad = 0;
#pragma unroll
        for (int k = 0; k < 3; k++) {
            uint4 a[6];
#pragma unroll
            for (int j = 0; j < 6; j++) a[j] = lds128(buf + l * 16 + k * 384 + j * 1152);
            float f[8] = {0.f, 0.f, 0.f, 0.f, 0.f, 0.f, 0.f, 0.f};
#pragma unroll
            for (int j = 0; j < 6; j++) add8(f, a[j]);
            bad = or3(bad | (a[4].x ^ tag), xor_or(a[0].x, a[1].x, tag), xor_or(a[2].x, a[3].x, tag));
            xw[k] = make_uint4(pack2(f[0], f[1]), pack2(f[2], f[3]), pack2(f[4], f[5]), pack2(f[6], f[7]));
        }
        if (!__any_sync(~0u, bad & 1)) break;
    }
}
__device__ __forceinline__ void ln_row(const Params& P, const uint4* xw, uint8_t* keep_at, uint8_t* img, int n, uint32_t* flag, int lane) {
    const int l = lane < 24 ? lane : 0;
    const float shift = bf_lo(__shfl_sync(~0u, xw[0].x, 0));
    float s = 0.f, q = 0.f;
#pragma unroll
    for (int k = 0; k < 3; k++) {
        float f[8] = {-shift, -shift, -shift, -shift, -shift, -shift, -shift, -shift};
        add8(f, xw[k]);
#pragma unroll
        for (int j = 0; j < 8; j++) { s += f[j]; q += f[j] * f[j]; }
    }
    if (lane >= 24) s = q = 0.f;
#pragma unroll
    for (int o = 16; o; o >>= 1) { s += __shfl_xor_sync(~0u, s, o); q += __shfl_xor_sync(~0u, q, o); }
    const float mean = s * (1.f / DM);
    const float rstd = rsqrtf(fmaxf(q * (1.f / DM) - mean * mean, 0.f) + 1e-5f), mu = shift + mean;
    const int row = ((n >> 1) & 3) * 8 + ((n >> 3) & 3) * 2 + (n & 33);
    img += row * 128;
    if (lane < 24) {
        uint8_t* d = img + (l >> 3) * 8192 + (l & 1) * 8;
        const uint32_t c0 = ((l & 6) ^ (row & 7)) << 4;
#define NRM(w) pack2((bf_lo(w) - mu) * rstd, (bf_hi(w) - mu) * rstd)
#pragma unroll
        for (int k = 0; k < 3; k++) {
            stg64(d + k * 24576 + c0, NRM(xw[k].x), NRM(xw[k].z));
            stg64(d + k * 24576 + (c0 ^ 16), NRM(xw[k].y), NRM(xw[k].w));
        }
#undef NRM
#pragma unroll
        for (int k = 0; k < 3; k++) stg128(keep_at + l * 16 + k * 384, xw[k]);
    }
    __syncwarp();
    const int j = lane < 18 ? lane : 0;
    const uint32_t v = ld_rlx((const uint32_t*)(j < 9 ? img + j * 8192 : keep_at + (j - 9) * 128));
    if (lane == 0) flag_signal_after(P, flag, v);
}
__device__ __forceinline__ void ln_first(const Params& P, int row0, int row1, int stride) {
    const int lane = threadIdx.x & 31, l = lane < 24 ? lane : 0;
#pragma unroll 1
    for (int tok = row0; tok < row1; tok += stride) {
        const uint8_t* src = (const uint8_t*)P.x + tok * 1152 + (l >> 1) * 32 + (l & 1) * 8;
        uint4 xw[3];
#pragma unroll
        for (int k = 0; k < 3; k++) {
            const uint2 a = __ldg((const uint2*)(src + k * 384)), b = __ldg((const uint2*)(src + k * 384 + 16));
            xw[k] = make_uint4(a.x, b.x, a.y, b.y);
        }
        ln_row(P, xw, g_res[0] + tok * 1152, g_xe + (tok >> 5) * XIMG, tok & 31, g_flag[F_XE][tok >> 5], lane);
    }
}
__device__ __forceinline__ void ln_job(const Params& P, int second, int j, int layer, int r, uint32_t epoch, uint32_t buf, uint32_t mb, uint32_t& ph) {
#define TOK ((j - layer * (LAG + second)) * 32 + r)
#define X1 (g_x1 + (((j + (second ? 0 : layer)) & (RING - 1)) * 64 + layer * 32 + r) * 1152)
    uint4 xw[3];
    {
        const uint32_t use = epoch * (NSTEP + second) + j;
        const int lane = fresh_tid() & 31;
        flag_poll(g_flag[F_PW + second][j], (epoch + 1) * NWO);
        fence_acq_gpu();
        fence_async_glb();
        TS(288, j, 10); TS(320, j, 13);
        sum_row(xw, g_part[second] + ((use & (RING - 1)) * 64 + layer * 32 + r) * 5760, second ? X1 : g_res[layer] + TOK * 1152, ((use / RING) & 1) ^ 1,
                buf, mb, ph, lane < 24 ? lane : 0);
        TS(288, j, 11); TS(320, j, 14);
    }
    j = keep(j);
    const int lane = fresh_tid() & 31, l = lane < 24 ? lane : 0, tok = TOK, n = layer * 32 + r;
    uint8_t* const x1 = X1;
#undef X1
#undef TOK
    if (second && layer) {
        if (lane < 24) {
            uint8_t* d = (uint8_t*)P.out + tok * 1152 + (l >> 1) * 32 + (l & 1) * 8;
#pragma unroll
            for (int k = 0; k < 3; k++) { stg64(d + k * 384, xw[k].x, xw[k].z); stg64(d + k * 384 + 16, xw[k].y, xw[k].w); }
        }
        if (lane == 0 && j + LAG + 1 < NSTEP) red_add_u32(g_flag[F_XE][j + LAG + 1], 1);
    } else {
        ln_row(P, xw, second ? g_res[1] + tok * 1152 : x1, second ? g_xe + (j + LAG) * XIMG : g_xf + ((j + layer) & (RING - 1)) * XIMG,
               second ? 32 + r : n, second ? g_flag[F_XE][j + LAG] : g_flag[F_XF][j + layer], lane);
    }
    TS(288, j, 12); TS(320, j, 15);
}

template <int KR, int WG>
__device__ __forceinline__ void load_wregs(uint32_t (&w)[KR][4], uint32_t sb) {
    const uint32_t base = frag_addr(sb);
    mbar_wait(sb + E_BAR + B_WL * 8, 0);
#pragma unroll
    for (int ks = 0; ks < E_ST1; ks++) ldsm4t(w[ks], base + e_stage(WG * E_ST1 + ks));
    nbar_sync(NB_ALL, NTHREADS);
    mbar_wait(sb + E_BAR + B_WL * 8, 1);
#pragma unroll
    for (int ks = E_ST1; ks < KR; ks++) ldsm4t(w[ks], base + e_stage(WG * E_ST1 + ks - E_ST1));
    cluster_sync_all();
    mbar_wait(sb + E_BAR + B_WS * 8, 0);
}
__host__ __device__ constexpr int m_pos(int tile) { return tile == 8 ? 0 : 1 + 2 * (tile & 3) + (tile >> 2); }
__host__ __device__ constexpr int m_off(int ks) { return m_pos(ks >> 2) * 128 + (ks & 3) * 16; }
template <int KR, bool LEAD>
__device__ __forceinline__ void proj_mem(uint64_t dw, float* d, const uint32_t (&w)[KR][4], uint32_t wss) {
    dw += m_off(KR - 1);
    wg_fence();
#pragma unroll
    for (int ks = 35; ks >= 0; ks--) {
        const uint64_t db = mkdesc(E_MEM, 128, 1024, 0) + m_off(ks);
        if (LEAD && 35 - ks == QK_LEAD) nbar_arrive(NB_QKI, NTHREADS);
        if (ks >= KR) wg_ss16<1>(d, mkdesc(wss + (ks - KR) * 2048, 1024, 1024, 1), db, ks < 35);
        else { wg_rs16<1>(d, w[ks < KR ? ks : 0], dw, 1); if (ks > 0) dmove(dw, m_off(ks - 1) - m_off(ks)); }
    }
    wg_commit();
}
template <int KR, bool WITHK>
__device__ __forceinline__ void proj_x(const Params& P, uint64_t& dx, uint64_t& dak, float* d, float* dk, const uint32_t (&w)[KR][4], uint32_t wss, int c) {
    if (c == 0 || c == 7) dx = P.dX[WITHK * 2 + (c == 7)] + x_slot(c) / 16;
    if (c == 0 && WITHK) dak = P.dXk + m_pos(0) * 512;
#pragma unroll
    for (int kk = 0; kk < 4; kk++) {
        const int ks = c * 4 + kk;
        if (WITHK) wg_ss64<0>(dk, dak, dx, ks > 0);
        if (ks < KR) wg_rs64<0>(d, w[ks < KR ? ks : 0], dx, ks > 0);
        else wg_ss64<0>(d, mkdesc(wss + (ks - KR) * 2048, 1024, 1024, 1), mkdesc(x_slot(c) + kk * 32, 1024, 1024, 1), ks > 0);
        if (ks < (WITHK ? 35 : KR - 1) && ks != 27) dmove(dx, kk < 3 ? 2 : (x_slot(c + 1) - x_slot(c)) / 16 - 6);
        if (ks < 35 && WITHK) dmove(dak, kk < 3 ? 128 : (m_pos(c + 1) - m_pos(c)) * 512 - 384);
    }
}
__device__ __forceinline__ void x_wait(uint32_t sb, int c, uint32_t par) {
    if (c == 0 || c == 2 || c == 4 || c == 5 || c == 7) mbar_wait(sb + E_BAR + (B_XF + c) * 8, par);
    wg_fence();
}
template <bool VPERM> __device__ __forceinline__ uint32_t tile_row(int tid, int rank) {
    const int w = (tid >> 5) & 3, g = (tid >> 2) & 7;
    return (rank * 64 + (VPERM ? (w >> 1) * 32 + (g >> 1) * 8 + (w & 1) * 4 + (g & 1) : w * 16 + g)) * 16;
}
template <bool VPERM>
__device__ __forceinline__ void put_mem(const float* d, uint32_t a, int rank, uint32_t peer_off, uint32_t mb) {
    const uint32_t p0 = pack2(d[0], d[1]), p1 = pack2(d[2], d[3]), p2 = pack2(d[4], d[5]), p3 = pack2(d[6], d[7]);
    constexpr int R = VPERM ? 32 : 128;
    st_async32(a + peer_off, rank ? p0 : p2, mb + peer_off);
    st_async32(a + R + peer_off, rank ? p1 : p3, mb + peer_off);
    sts32(a, rank ? p2 : p0);
    sts32(a + R, rank ? p3 : p1);
}
#define XCOL(c) "r"(pack2(e[16 * c], e[16 * c + 1])), "r"(pack2(e[16 * c + 4], e[16 * c + 5])), "r"(pack2(e[16 * c + 8], e[16 * c + 9])), "r"(pack2(e[16 * c + 12], e[16 * c + 13]))
__device__ __forceinline__ void put_xv(const float* d, uint32_t a, int rank, uint32_t peer_off, uint32_t mb) {
#pragma unroll
    for (int h = 0; h < 2; h++) {
        const float* e = d + 2 * h;
        asm volatile("{.reg .pred p; setp.ne.s32 p, %11, 0;"
                     "@p st.async.shared::cluster.mbarrier::complete_tx::bytes.v4.b32 [%9], {%0,%1,%2,%3}, [%10];"
                     "@!p st.async.shared::cluster.mbarrier::complete_tx::bytes.v4.b32 [%9], {%4,%5,%6,%7}, [%10];"
                     "@p st.shared.v4.b32 [%8], {%4,%5,%6,%7}; @!p st.shared.v4.b32 [%8], {%0,%1,%2,%3};}"
                     :: XCOL(0), XCOL(1), "r"(a + h * 32), "r"(a + h * 32 + peer_off), "r"(mb + peer_off), "r"(rank) : "memory");
    }
}
__device__ __forceinline__ void park_x(const float* d, uint32_t a0, uint32_t a1) {
#pragma unroll
    for (int h = 0; h < 2; h++) {
        const float* e = d + 2 * h;
        asm volatile("st.shared.v4.b32 [%8], {%0,%1,%2,%3}; st.shared.v4.b32 [%9], {%4,%5,%6,%7};"
                     :: XCOL(0), XCOL(1), "r"(a0 + h * 128), "r"(a1 + h * 128) : "memory");
    }
}
#undef XCOL
__device__ __forceinline__ void warp_arrive(uint32_t b) { __syncwarp(); if ((threadIdx.x & 31) == 0) mbar_arrive(b); }

__device__ __forceinline__ void x_load(uint32_t sb, const uint8_t* img, int c) {
    const uint32_t bytes = c == 4 ? 8192 : 16384;
    mbar_expect(sb + E_BAR + (B_XF + c) * 8, bytes);
    bulk_g2s(sb + x_slot(c), img + c * 8192, bytes, sb + E_BAR + (B_XF + c) * 8);
}
__device__ __forceinline__ void x_ready(int step, uint32_t e1) {
    const uint32_t target = e1 * 32 * ((step < NSEG) + (step >= LAG) + (step > 2 * LAG + 1));
    int n = 0;
    while ((int)(ld_rlx(g_flag[F_XE][step]) - target) < 0) { SPIN_CHECK(n, 3); }
    fence_acq_gpu();
    fence_async_glb();
}

__device__ __forceinline__ void softmax_rows(const float* p, const float* q, uint32_t* pk, uint32_t* qk) {
    float mp = fmaxf(fmaxf(fmaxf(p[0], p[1]), fmaxf(p[2], p[3])), fmaxf(fmaxf(fmaxf(p[4], p[5]), fmaxf(p[6], p[7])), fmaxf(p[8], p[9])));
    float mq = fmaxf(fmaxf(q[0], q[1]), fmaxf(q[2], q[3]));
#pragma unroll
    for (int o = 1; o <= 2; o++) { mp = fmaxf(mp, __shfl_xor_sync(~0u, mp, o)); mq = fmaxf(mq, __shfl_xor_sync(~0u, mq, o)); }
    mp *= SM_SCALE * LOG2E;
    mq *= SM_SCALE * LOG2E;
#pragma unroll
    for (int j = 0; j < 5; j++) pk[j] = pack2(ex2(fmaf(p[2 * j], SM_SCALE * LOG2E, -mp)), ex2(fmaf(p[2 * j + 1], SM_SCALE * LOG2E, -mp)));
#pragma unroll
    for (int j = 0; j < 2; j++) qk[j] = pack2(ex2(fmaf(q[2 * j], SM_SCALE * LOG2E, -mq)), ex2(fmaf(q[2 * j + 1], SM_SCALE * LOG2E, -mq)));
}

template <int N>
__device__ __forceinline__ uint32_t reduce_unit(const CUtensorMap* tm, int x, int y, uint32_t buf, uint32_t mb, uint32_t& ph, uint32_t tag, int lane, int& n, uint32_t prof_at) {
    const bool one = elect();
#pragma unroll 1
    while (true) {
        if (one && (N == 16 || n > 0)) { mbar_expect(mb, N * 128); tma_2d(buf, tm, x, y, mb); }
        SPIN_CHECK(n, 1);
        mbar_wait(mb, ph);
        ph ^= 1;
        float a[4];
        uint32_t v[N];
#pragma unroll
        for (int j = 0; j < N; j++) v[j] = lds32(buf + lane * 4 + j * 128);
#pragma unroll
        for (int j = 0; j < N; j++) {
            const int k = N == 16 ? 2 * (j & 1) : 0;
            a[k] = j < N / 8 ? bf_lo(v[j]) : a[k] + bf_lo(v[j]);
            a[k + 1] = j < N / 8 ? bf_hi(v[j]) : a[k + 1] + bf_hi(v[j]);
        }
        uint32_t bad = or3(xor_or(v[0], v[1], tag), xor_or(v[2], v[3], tag), xor_or(v[4], v[5], tag));
        if (N == 16) {
            bad = or3(bad, or3(xor_or(v[6], v[7], tag), xor_or(v[8], v[9], tag), xor_or(v[10], v[11], tag)), xor_or(v[12], v[13], tag));
            a[0] += a[2]; a[1] += a[3];
        }
#pragma unroll
        for (int o = 16; o >= (N == 16 ? 16 : 4); o >>= 1) { a[0] += __shfl_xor_sync(~0u, a[0], o); a[1] += __shfl_xor_sync(~0u, a[1], o); }
        if (!(__ballot_sync(~0u, or_bit0(bad, xor_or(v[N - 2], v[N - 1], tag))) & 0x11111111u)) return pack2(a[0], a[1]);
    }
}
__device__ __forceinline__ uint32_t ag_place(int tile, int layer, int t, int up, bool writes) {
    const int f = (blockIdx.x >> 4) * 16 + ((blockIdx.x >> 1) & 7) + up * 8;
    return opaque((m_pos(tile) * 128 + layer * 64 + f) * 16 + t * 4 + (((f >> 3) & 3) == t) + (writes ? 0 : 2));
}
__device__ __forceinline__ uint32_t mem0_word(const Params& P, int tile, uint32_t ag_dst) {
    const uint16_t* m = (const uint16_t*)P.mem0 + tile * 64 + ((ag_dst >> 4) & 63) + ((ag_dst >> 2) & 3) * (2 * DM);
    return (uint32_t)__ldg(m) | ((uint32_t)__ldg(m + DM) << 16);
}
__device__ __forceinline__ void ag_store(uint8_t* to, uint32_t w, uint32_t ag_dst, uint32_t atag) {
    asm volatile("{.reg .pred p; setp.eq.u32 p, %2, 0; @p st.relaxed.gpu.global.u32 [%0], %1;}" :: "l"(to), "r"(tagged(w, ag_dst & 1, atag)), "r"(ag_dst & 2) : "memory");
}

__device__ __forceinline__ void engine_a(const Params& P, uint32_t sb) {
    const uint32_t bars = sb + E_BAR;
    uint32_t w[KRQ][4];
    load_wregs<KRQ, 0>(w, sb);
    const int rank = blockIdx.x & 1;
    const uint32_t peer_off = mapa(sb, rank ^ 1) - sb;
    const int tid = opaque(threadIdx.x);
    const bool warp0 = __shfl_sync(~0u, tid, 0) == 0, lane0 = (tid & 31) == 0;
    const uint32_t row = opaque(sb + tile_row<false>(tid, rank));
    const int dq = opaque((tid >> 2) - 2 * (tid & 3));
#pragma unroll 1
    for (int i = 0; i < NSTEP; i++) {
        {
            const uint32_t xp = i & 1;
            float xq[32], xk[32], d[8];
            uint64_t dx, dak;
#define XA(c) x_wait(sb, c, xp); proj_x<KRQ, true>(P, dx, dak, xq, xk, w, E_WQ, c); wg_commit()
            if (i > 0) nbar_sync(NB_WIA, 256);
            XA(0); XA(1); XA(2);
            wg_wait<1>();
            if (lane0) mbar_arrive(bars + B_E01 * 8);
            ES(0, 8);
            XA(3); XA(4);
            wg_wait<1>();
            if (lane0) mbar_arrive(bars + B_MF * 8);
            ES(0, 9);
            XA(5); XA(6); XA(7);
            wg_wait<1>();
            if (lane0) { mbar_arrive_remote(bars + B_TF * 8 + peer_off); mbar_arrive(bars + B_TF * 8); }
            XA(8);
#undef XA
            nbar_arrive(NB_XI, 256);
            const uint32_t t = keep(tid) & 3, own = row + t * (2 * TG), out = row - rank * 1024 + E_OUT + t * SG;
            ES(0, 10);
            mbar_wait(bars + B_TF * 8, xp);
            wg_wait<0>();
            park_x(xk, rank ? out : own + E_KX, rank ? own + E_KX : out);
            park_x(xq, rank ? out + 4 * SG : own + E_QX, rank ? own + E_QX : out + 4 * SG);
            fence_async_smem();
            __syncwarp();
            if (lane0) mbar_arrive(bars + B_RF * 8);
            ES(0, 11);
            nbar_sync(NB_MA, 256);
            proj_mem<KRQ, true>(P.dMq, d, w, E_WQ);
            wg_wait<0>();
            put_mem<false>(d, row + E_QM + t * 4, rank, peer_off, bars + B_QK * 8);
            __syncwarp();
            if (lane0) { mbar_expect(bars + B_QK * 8, (2048 + 8192) / 4); mbar_arrive(bars + B_PD * 8); }
        }
        const uint32_t par = i & 1;
        ES(0, 1);
        uint32_t pa[12];
        {
            float s[20];
            uint64_t da = P.dQ, db = P.dK;
            mbar_wait_cl(bars + B_QK * 8, par);
            fence_async_smem();
            ES(0, 2);
            wg_fence();
#pragma unroll
            for (int ks = 0; ks < 8; ks++) { wg_ss40<1>(s, da, db, ks > 0); if (ks < 7) { dmove(da, 16); dmove(db, 16); } }
            wg_commit();
            nbar_arrive(NB_SI, 256);
            wg_wait<0>();
            ES(0, 3);
            constexpr float MASKED = -1e9f / SM_SCALE;
            float p[10];
            uint32_t pk[5], qk[2];
#pragma unroll
            for (int j = 0; j < 10; j++) p[j] = (j >= 8 || (j >> 1) * 8 + (j & 1) <= dq) ? s[(j >> 1) * 4 + (j & 1)] : MASKED;
            const float q[4] = {p[0], p[1], p[8], p[9]};
#pragma unroll
            for (int j = 0; j < 10; j++) if (warp0) p[j] = s[(j >> 1) * 4 + 2 + (j & 1)];
            softmax_rows(p, q, pk, qk);
#pragma unroll
            for (int m = 0; m < 5; m++) { pa[2 * m] = !warp0 ? pk[m] : m == 0 ? qk[0] : m == 4 ? qk[1] : 0; pa[2 * m + 1] = pk[m]; }
            pa[10] = keep(0);
            pa[11] = keep(0);
        }
        {
            float o[64];
            ES(0, 4);
            mbar_wait_cl(bars + B_V * 8, par);
            fence_async_smem();
            wg_fence();
            wg_rs128<0>(o, &pa[0], mkdesc(E_VX, 2 * TG, 128, 0), 0);
            wg_rs128<0>(o, &pa[4], mkdesc(E_VX + 4 * TG, 2 * TG, 128, 0), 1);
            wg_rs128<0>(o, &pa[8], mkdesc(E_VM, 0, 128, 0), 1);
            wg_commit();
            nbar_arrive(NB_PVI, 256);
            const uint2 sel = lds64(sb + E_SEL);
#define BOTH(w) (__uint_as_float(__byte_perm(w, 0, sel.x)) + __uint_as_float(__byte_perm(w, 0, sel.y)))
            float s0 = BOTH(pa[0]) + BOTH(pa[8]), s1 = (BOTH(pa[1]) + BOTH(pa[3])) + (BOTH(pa[5]) + BOTH(pa[7])) + BOTH(pa[9]);
#undef BOTH
#pragma unroll
            for (int x = 1; x <= 2; x++) { s0 += __shfl_xor_sync(~0u, s0, x); s1 += __shfl_xor_sync(~0u, s1, x); }
            const float inv0 = rcp(warp0 ? s0 : s1), inv1 = rcp(s1);
            const int t = keep(tid);
            const uint32_t a = keep(sb + E_OM + rank * 2048 + (t >> 2) * 128 + (((t ^ (t >> 2)) & 3) << 4) + (t & 16) * 4);
            uint8_t* dst = g_o + ((i & (RING - 1)) * 64 + (blockIdx.x & ~1)) * 8192 + rank * 2048 + keep((t >> 2) * 64 + (((t ^ (t >> 3)) & 3) << 4));
            wg_wait<0>();
            ES(0, 6);
#define OW(j, h) pack2(o[4 * (j) + 2 * (h)] * ((h) ? inv1 : inv0), o[4 * (j) + 2 * (h) + 1] * ((h) ? inv1 : inv0))
#define OCHUNK(jj, h) make_uint4(OW(4 * (jj), h), OW(4 * (jj) + 1, h), OW(4 * (jj) + 2, h), OW(4 * (jj) + 3, h))
            if (warp0) {
#pragma unroll
                for (int jj = 0; jj < 4; jj++) {
                    const uint4 v = OCHUNK(jj, 1);
                    const uint32_t b = (a ^ ((jj & 1) * 64)) + (jj >> 1) * 1024;
                    st_async128(b + peer_off, v, bars + B_OM * 8 + peer_off);
                    sts128(b, v);
                }
                __syncwarp();
            }
            if (lane0) mbar_expect(bars + B_OM * 8, 2048 / 4);
            ES(0, 7);
            if (rank ? i >= LAG : i < NSEG) {
#pragma unroll
                for (int jj = 0; jj < 4; jj++) stg128(dst + jj * 4096, OCHUNK(jj, 0));
            }
#undef OCHUNK
#undef OW
            nbar_arrive(NB_WIB, NTHREADS);
        }
    }
    mbar_wait(bars + B_OM * 8, (NSTEP - 1) & 1);
}

__device__ __forceinline__ void engine_b(const Params& P, uint32_t sb) {
    const uint32_t bars = sb + E_BAR;
    uint32_t w[KRV][4];
    load_wregs<KRV, 1>(w, sb);
    const int rank = blockIdx.x & 1;
    const uint32_t peer_off = mapa(sb, rank ^ 1) - sb;
    const int tid = threadIdx.x & 127, warp = __shfl_sync(~0u, tid >> 5, 0);
    const bool lane0 = opaque(tid & 31) == 0;
    const uint32_t ax = opaque(sb + E_VX + tile_row<true>(tid, rank) + (tid & 3) * (2 * TG));
    const uint32_t am = opaque(sb + E_VM + tile_row<true>(tid, rank) + (tid & 3) * 4);
    const int kg = ((blockIdx.x & ~1) + tid) / 13;
    const uint32_t oflag = opaque(tid == 0 || (tid == 1 && kg * 13 == (blockIdx.x | 1)) ? (F_O + kg) * sizeof(g_flag[0]) : 0);
    const uint32_t e1 = __shfl_sync(~0u, lds32(sb + E_EPOCH), 0) + 1;
    const uint32_t ag_dst = ag_place(8, rank, tid & 3, warp & 1, (tid & 31) < 4);
    uint32_t ph = 0;
    const uint8_t* img = g_xe;
    if (warp == 0) {
        x_ready(0, e1);
        fence_async_smem();
        if (elect()) { x_load(sb, img, 0); x_load(sb, img, 2); }
    }
#pragma unroll 1
    for (int i = 0; i < NSTEP; i++) {
        {
            const uint32_t xp = i & 1;
            float xv[32];
            uint64_t dx;
#define XB(c) x_wait(sb, c, xp); proj_x<KRV, false>(P, dx, dx, xv, xv, w, E_WV, c); wg_commit()
#pragma unroll
            for (int c = 0; c < GB1; c++) { XB(c); }
            if (i > 0) nbar_sync(NB_PVI, 256);
#pragma unroll
            for (int c = GB1; c < GB1 + GB2; c++) { XB(c); }
            ES(128, 14);
            if (warp == 0) {
                if (i > 0) mbar_wait(bars + B_OM * 8, xp ^ 1);
                if (elect()) { x_load(sb, img, 4); x_load(sb, img, 5); }
            }
            wg_wait<0>();
            if (lane0) { mbar_arrive(bars + B_E01 * 8); mbar_arrive(bars + B_MF * 8); }
            if (i > 0) nbar_sync(NB_WIB, NTHREADS);
#pragma unroll
            for (int c = 4; c < 4 + GB3; c++) { XB(c); }
            if (warp == 0) {
                if (i > 0) {
                    const int l1 = fresh_tid() & 31;
                    const uint8_t* o = g_o + (((i - 1) & (RING - 1)) * 64 + (blockIdx.x & ~1)) * 8192 + rank * 2048 + (l1 >> 4) * 4096 + (l1 & 15) * 128;
                    const uint32_t v = ld_rlx((const uint32_t*)o) | ld_rlx((const uint32_t*)(o + 8192));
                    if (oflag) flag_signal_after(P, (uint32_t*)((uint8_t*)g_flag[0][i - 1] + oflag), v);
                    ES(0, 17);
                }
            } else if (warp == 1) {
                mbar_wait(bars + B_E01 * 8, xp);
                if (X7_DELAY) spin_cycles(X7_DELAY);
                if (elect()) x_load(sb, img, 7);
            } else if (warp >= 2) {
                const uint32_t ra = (e1 - 1) * NSTEP + i, rr = ra - e1;
                uint32_t w9;
                if (i > 0) {
                    int n = 0;
                    const int l1 = fresh_tid() & 31;
                    ES(192, 12);
                    w9 = reduce_unit<8>(&P.tmR9, 1792 + rank * 256 + warp * 128 + (blockIdx.x >> 1) * 4, (rr & 1) * 64, sb + E_RS + 6144 + warp * 1024, bars + (B_R9 - 2 + warp) * 8, ph,
                                           ((rr >> 1) & 1) ^ 1, l1, n, sb + E_BAR + 128 + (xp ^ 1) * 128 + 29 * 4);
                    EV(192, 25, n - 1);
                }
                if (i == 0 || (rank && i == LAG)) w9 = mem0_word(P, 8, keep(ag_dst));
                ag_store(g_ag + ((ra & 1) * 18432 + (ag_dst & ~3u)), w9, ag_dst, ((ra >> 1) & 1) ^ 1);
                ES(192, 0);
            }
            ES(128, 28);
#pragma unroll
            for (int c = 4 + GB3; c < 7; c++) { XB(c); }
            wg_wait<0>();
            if (lane0) { mbar_arrive_remote(bars + B_TF * 8 + peer_off); mbar_arrive(bars + B_TF * 8); }
            nbar_sync(NB_XI, 256);
            XB(7); XB(8);
#undef XB
            wg_wait<0>();
            if (lane0) mbar_arrive(bars + B_RF * 8);
            ES(128, 15);
            img += XIMG;
            if (warp == 1 && i < NSTEP - 1) x_ready(i + 1, e1);
            mbar_wait(bars + B_TF * 8, xp);
            mbar_wait(bars + B_M * 8, xp);
            if (warp < 2) {
                mbar_wait(bars + B_RF * 8, xp);
                if (elect()) {
                    if (warp == 0) {
#pragma unroll 1
                        for (int j = 0; j < 4; j++) {
                            const uint32_t o = sb + j * (2 * TG) + rank * 1024 + peer_off;
                            bulk_s2peer(o + E_KX, sb + E_OUT + j * SG, 1024, bars + B_QK * 8 + peer_off);
                            bulk_s2peer(o + E_QX, sb + E_OUT + (j + 4) * SG, 1024, bars + B_QK * 8 + peer_off);
                        }
                    } else if (i < NSTEP - 1) {
                        x_load(sb, img, 0);
                    }
                }
            }
            put_xv(xv, ax, rank, peer_off, bars + B_V * 8);
        }
        ES(128, 16);
        float d[8];
        nbar_sync(NB_QKI, NTHREADS);
        proj_mem<KRV, false>(P.dMv, d, w, E_WV);
        wg_wait<0>();
        put_mem<true>(d, am, rank, peer_off, bars + B_V * 8);
        __syncwarp();
        if (lane0) { mbar_expect(bars + B_V * 8, (1024 + 4096) / 4); mbar_arrive(bars + B_PD * 8); }
        ES(128, 18);
        nbar_sync(NB_SI, 256);
    }
    nbar_sync(NB_PVI, 256);
    nbar_sync(NB_WIB, NTHREADS);
    if (oflag) flag_signal((uint32_t*)((uint8_t*)g_flag[0][NSTEP - 1] + oflag));
}

__device__ __forceinline__ void engine_c(const Params& P, uint32_t sb) {
    const uint32_t bars = sb + E_BAR;
    const int e = blockIdx.x, rank = e & 1;
    const int tid = opaque(threadIdx.x & 127), lane = tid & 31, warp = __shfl_sync(~0u, tid >> 5, 0);
    if (warp == 0) {
        if (lane == 0) mbar_expect(bars + B_WL * 8, 2 * E_ST1 * 2048);
        __syncwarp();
        if (lane < E_ST1) {
            tma_w(sb + e_stage(lane), &P.tmWq, lane, e, bars + B_WL * 8);
            tma_w(sb + e_stage(E_ST1 + lane), &P.tmWv, lane, e, bars + B_WL * 8);
        }
        if (E_ST1 + lane < KRQ) tma_w_prefetch(&P.tmWq, E_ST1 + lane, e);
        if (E_ST1 + lane < KRV) tma_w_prefetch(&P.tmWv, E_ST1 + lane, e);
    } else if (warp == 1) {
        if (lane == 0) mbar_expect(bars + B_WS * 8, E_RING);
        __syncwarp();
        for (int ks = lane; ks < 36; ks += 32) tma_w(sb + E_WK + (m_pos(ks >> 2) * 4 + (ks & 3)) * 2048, &P.tmWk, ks, e, bars + B_WS * 8);
        if (lane < 36 - KRQ) tma_w(sb + E_WQ + lane * 2048, &P.tmWq, KRQ + lane, e, bars + B_WS * 8);
        if (lane < 36 - KRV) tma_w(sb + E_WV + lane * 2048, &P.tmWv, KRV + lane, e, bars + B_WS * 8);
        tma_w(sb + E_WO + lane * 2048, &P.tmWo, (e >> 1) * 8 + (lane & 7), rank * 4 + (lane >> 3), bars + B_WS * 8);
        if (lane < 4) tma_w(sb + E_WO + (32 + lane) * 2048, &P.tmWo, e * 4 + lane, 8, bars + B_WS * 8);
    }
    nbar_sync(NB_ALL, NTHREADS);
    if (warp == 0) {
        if (lane == 0) { fence_async_smem(); mbar_expect(bars + B_WL * 8, (KRQ + KRV - 2 * E_ST1) * 2048); }
        __syncwarp();
        if (E_ST1 + lane < KRQ) tma_w(sb + e_stage(lane), &P.tmWq, E_ST1 + lane, e, bars + B_WL * 8);
        if (E_ST1 + lane < KRV) tma_w(sb + e_stage(E_ST1 + lane), &P.tmWv, E_ST1 + lane, e, bars + B_WL * 8);
    }
    cluster_sync_all();
    mbar_wait(bars + B_WS * 8, 0);
    const uint32_t peer_off = mapa(sb, rank ^ 1) - sb;
    const uint32_t epoch = __shfl_sync(~0u, lds32(sb + E_EPOCH), 0);
    const uint32_t ag_dst = ag_place(rank * 4 + warp, (lane >> 1) & 1, (lane >> 2) & 3, lane & 1, lane < 16), w_init = mem0_word(P, rank * 4 + warp, ag_dst);
    const uint32_t k_dst = opaque(sb + E_KM + tile_row<false>(tid, rank) + (tid & 3) * 4);
    const bool lane0 = lane == 0;
    uint32_t rr = epoch * (NSTEP - 1) - 1, ra = epoch * NSTEP, ph = 0, ak = 0;
#pragma unroll 1
    for (int i = -1; i < NSTEP; i++, rr++, ra++) {
        const uint32_t par = i & 1;
        uint32_t w0 = w_init;
        const uint32_t atag = ((ra >> 1) & 1) ^ 1;
        uint8_t* const ag_to = g_ag + ((ra & 1) * 18432 + (ag_dst & ~3u));
        if (i >= 0) {
            const uint32_t tag = ((rr >> 1) & 1) ^ 1;
            uint32_t mine, latest;
            {
                float d[8];
                uint64_t da = P.dWk, db = P.dMk;
                wg_fence();
#pragma unroll
                for (int j = 0; j < 36; j++) {
                    if (j == QK_LEAD) nbar_arrive(NB_QKI, NTHREADS);
                    wg_ss16<1>(d, da, db, j > 0);
                    if (j < 35) { dmove(da, 128); dmove(db, (j & 3) < 3 ? 16 : 80); }
                }
                wg_commit();
                wg_wait<0>();
                put_mem<false>(d, k_dst, rank, peer_off, bars + B_QK * 8);
                __syncwarp();
                if (lane0) mbar_arrive(bars + B_QK * 8);
                if (lane0) mbar_arrive(bars + B_PD * 8);
                ES(256, 13);
                if (i == NSTEP - 1) break;
                mbar_wait(bars + B_QK * 8, par);
                unsigned long long now;
                asm volatile("mov.u64 %0, %%globaltimer;" : "=l"(now));
                const uint32_t t0 = clock32();
                if (tid == 0) asm volatile("red.relaxed.gpu.global.max.u64 [%0], %1;" :: "l"(&g_latest), "l"(now) : "memory");
                mine = (uint32_t)now;
                if (warp == 3) {
                    mbar_wait(bars + B_PD * 8, par);
                    if (elect()) x_load(sb, g_xe + (i + 1) * XIMG, 2);
                    EFLUSH(i - 1);
                }
                while ((int)(clock32() - t0) < LATE_WAIT) {}
                latest = ld_rlx((const uint32_t*)&g_latest);
            }
            {
                float y[4][8];
                uint64_t db = P.dOm + rank * 64, da = P.dWo + 32 * 128;
                uint8_t* const dst = g_rs + (size_t)opaque(((rr & 1) * NENG + e) * 10240 + tid * 16);
#define W_TILE(Y, F) { _Pragma("unroll") for (int ks = 0; ks < 8; ks++) { wg_ss16<0>(y[Y], da, db, ks > 0 ? 1 : F); dmove(da, 128); dmove(db, ks == 7 ? -70 : ks == 3 ? 58 : 2); } wg_commit(); }
#define TAGGED(a, b) ((pack2(a, b) & ~1u) | tag)
#define W_ST(Y, T) { st_rlx128(dst + (T) * 2048, make_uint4(TAGGED(y[Y][0], y[Y][1]), pack2(y[Y][2], y[Y][3]), pack2(y[Y][4], y[Y][5]), pack2(y[Y][6], y[Y][7]))); __syncwarp(); }
                mbar_wait_cl(bars + B_OM * 8, par);
                fence_async_smem();
                ES(256, 19);
                wg_fence();
#pragma unroll
                for (int ks = 0; ks < 4; ks++) { wg_ss16<0>(y[0], da, db, ks > 0); dmove(da, ks < 3 ? 128 : -35 * 128); if (ks < 3) dmove(db, 2); }
                wg_commit();
                db = P.dOm;
                W_TILE(1, 0);
                W_TILE(2, 0);
                wg_wait<2>();
#pragma unroll
                for (int k = 0; k < 4; k++) st_rlx32(dst + 8192 + k * 512 - tid * 12, tagged(pack2(y[0][2 * k], y[0][2 * k + 1]), (tid & 3) == 0, tag));
                __syncwarp();
                wg_fence();
                W_TILE(3, 0);
                wg_wait<2>(); W_ST(1, 0);
                wg_fence();
                W_TILE(0, -1);
                wg_wait<2>(); W_ST(2, 1);
                wg_wait<1>(); W_ST(3, 2);
                nbar_arrive(NB_WIB, NTHREADS);
                nbar_arrive(NB_WIA, 256);
                wg_wait<0>(); W_ST(0, 3);
#undef W_TILE
#undef W_ST
#undef TAGGED
            }
            const uint32_t t0 = clock32();
            ES(352, 20);
            const int w1 = keep(warp), x0 = rank * 2560 + w1 * 512 + (e >> 1) * 16;
            const int lag = min(max((int)(latest - mine), 0), 600) * LATE_MUL / 4, dly = RS_DELAY - (3 - w1) * RS_SKEW + lag;
            int n = 0;
            EV(0, 30, dly);
            if (w1 >= 2) {
                while ((int)(clock32() - t0) < RS_DELAY0 + lag) {}
                if (elect()) {
                    mbar_expect(bars + (B_R9 - 2 + w1) * 8, 1024);
                    tma_2d(sb + E_RS + 6144 + w1 * 1024, &P.tmR9, 1792 + rank * 256 + w1 * 128 + (e >> 1) * 4, (rr & 1) * 64, bars + (B_R9 - 2 + w1) * 8);
                }
            }
            while ((int)(clock32() - t0) < dly) {}
            w0 = reduce_unit<16>(&P.tmRs, x0, (rr & 1) * 32, sb + E_RS + w1 * 2048, bars + (B_RS + w1) * 8, ph, tag, keep(tid) & 31, n, sb + E_BAR + 128 + par * 128 + 21 * 4);
            EV(352, 26, n - 1);
            if (i == LAG - 1 && (ag_dst & 1024)) w0 = w_init;
        }
        ag_store(ag_to, w0, ag_dst, atag);
        ES(352, 22);
        if (lane0) { mbar_arrive_remote(bars + B_TF * 8 + peer_off); mbar_arrive(bars + B_TF * 8); }
        const int w1 = keep(warp), l1 = keep(tid) & 31;
        const uint32_t dst = sb + E_MEM + w1 * 4608, mb = bars + (B_AG + w1 * 2) * 8, chk = dst + l1 * 16 + (l1 >> 3) * 4;
        const uint8_t* src = g_ag + ((ra & 1) * 18432 + w1 * 4608);
        const bool one = elect();
        mbar_wait(bars + B_MF * 8, par ^ 1);
        const uint32_t t1 = clock_after(nbar_any(NB_C, 128, 0));
        int n = 0;
        while ((int)(clock32() - t1) < AG_DELAY) {}
#pragma unroll 1
        while (true) {
            if (one) { mbar_expect(mb, 4608); bulk_g2s(dst, src, 4608, mb); }
            mbar_wait(mb, ak & 1);
            ak++;
            uint32_t v[9];
#pragma unroll
            for (int j = 0; j < 9; j++) v[j] = lds32(chk + j * 512);
            if (!__any_sync(~0u, or_bit0(xor_or(v[0], v[1], atag) | xor_or(v[2], v[3], atag) | xor_or(v[4], v[5], atag), xor_or(v[6], v[7], atag) | (v[8] ^ atag)))) break;
            SPIN_CHECK(n, 2);
        }
        ES(352, 23); EV(352, 27, n);
        nbar_arrive(NB_MA, 256);
        if (lane0) mbar_arrive(bars + B_M * 8);
        nbar_sync(NB_C, 128);
    }
    nbar_arrive(NB_WIB, NTHREADS);
    if (e == 0 && tid == 0) g_epoch = lds32(sb + E_EPOCH) + 1;
}

enum { ST_WO = 0, ST_F2 = 1, ST_F1 = 2 };
template <int ST> struct Stage;
template <> struct Stage<ST_WO> { static constexpr int NKS = 52, NR0 = 37, NR1 = 45, NT1 = 1, NSLOT = 8, TB = 0; };
template <> struct Stage<ST_F2> { static constexpr int NKS = 58, NR0 = 37, NR1 = 45, NT1 = 1, NSLOT = 5, TB = 1; };
template <> struct Stage<ST_F1> { static constexpr int NKS = 36, NR0 = F1_NR, NR1 = F1_NR, NT1 = 2, NSLOT = F1_SLOTS, TB = 0; };
template <int ST> struct StageMap : Stage<ST> {
    using S = Stage<ST>;
    static constexpr int NCH = (S::NKS + 3) / 4;
    static constexpr int W0A = 0, W0B = W0A + (S::NKS - S::NR0) * 2048, W1A = W0B + S::NKS * 2048, W1B = W1A + (S::NKS - S::NR1) * 2048;
    static constexpr int RNG = W1B + (S::NT1 - 1) * S::NKS * 2048;
    static constexpr int ROWS = RNG + S::NSLOT * 8192, NIT = ST == ST_WO ? NSTEP : NROUND;
    static_assert(ROWS + (ST == ST_F1 ? 3 * 6912 : 0) <= SM_BAR && (S::NR0 + S::NR1) * 2048 <= SM_BAR, "stage smem");
};
__host__ __device__ constexpr int rs_idx(int ks, int nr, int nks) { return ks * nr / nks; }
__host__ __device__ constexpr bool is_rs(int ks, int nr, int nks) { return rs_idx(ks + 1, nr, nks) > rs_idx(ks, nr, nks); }

template <int ST, int SHAPE>
__device__ __forceinline__ void stage_consumer(const Params& P, uint32_t sb, int idx, const int WG) {
    using M = StageMap<ST>;
    constexpr int NR = SHAPE ? M::NR1 : M::NR0, NT = SHAPE ? M::NT1 : 2, NKS = M::NKS;
    const uint32_t bars = sb + SM_BAR;
    uint32_t w[NR][4];
    {
        const uint32_t base = frag_addr(sb + WG * (M::NR0 * 2048));
        mbar_wait(bars + B_WL * 8, 0);
#pragma unroll
        for (int r = 0; r < NR; r++) ldsm4t(w[r], base + r * 2048);
        nbar_sync(NB_ALL, 288);
        mbar_wait(bars + B_WS * 8, 0);
    }
    const bool shortk = ST != ST_F1 && idx >= 12;
    uint32_t s = 0, ph = 0, use = __shfl_sync(~0u, lds32(sb + SM_EPOCH), 0) * M::NIT;
#pragma unroll 1
    for (int j = 0; j < M::NIT; j++, use++) {
        float d[NT][32];
        uint64_t da0 = P.d128 + WG * (M::W1A / 16), da1 = da0 + (NKS - NR) * 128;
        uint32_t prev = 0;
#pragma unroll
        for (int c = 0; c < M::NCH; c++) {
            if (c < M::NCH - 1 || !shortk) {
                mbar_wait(bars + (B_FULL + s) * 8, ph);
                if (c == 0) TS(WG * 128, j, WG * 4);
                uint64_t b = (ST == ST_WO ? P.d64 : P.d128) + (M::RNG / 16 + s * 512);
                wg_fence();
#pragma unroll
                for (int kk = 0; kk < 4; kk++) {
                    const int ks = c * 4 + kk;
                    if (ks < NKS) {
                        if (is_rs(ks, NR, NKS)) wg_rs64<M::TB>(d[0], w[rs_idx(ks, NR, NKS)], b, ks > 0);
                        else { wg_ss64<M::TB>(d[0], da0, b, ks > 0); dmove(da0, 128); }
                        if (NT > 1) { wg_ss64<M::TB>(d[NT - 1], da1, b, ks > 0); dmove(da1, 128); }
                        if (kk < 3) dmove(b, ST == ST_WO ? (kk == 1 ? 254 : 2) : M::TB ? 128 : 2);
                    }
                }
                wg_commit();
                if (c > 0) {
                    wg_wait<1>();
                    if ((fresh_tid() & 31) == 0) mbar_arrive(prev);
                }
                prev = bars + (B_EMPTY + s) * 8;
                if (++s == M::NSLOT) { s = 0; ph ^= 1; }
            }
        }
        const int tid = fresh_tid(), g = (tid >> 2) & 7, t = tid & 3, warp = (tid >> 5) & 3;
        wg_wait<0>();
        if ((tid & 31) == 0) mbar_arrive(prev);
        TS(WG * 128, j, WG * 4 + 1);
        if (ST == ST_F1) {
            uint8_t* dst = g_h + ((j & (RING - 1)) * FF + idx * 128 + WG * 64 + warp * 16 + g) * 128;
#pragma unroll
            for (int h = 0; h < 2; h++) {
#pragma unroll
                for (int c = 0; c < 2; c++) {
                    uint32_t pk[4];
#pragma unroll
                    for (int m = 0; m < 4; m++) {
                        const int o = 16 * c + 4 * m + 2 * h;
                        const float g0 = d[0][o], g1 = d[0][o + 1];
                        const float e0 = 1.f + ex2(fminf(-LOG2E * g0, 60.f)), e1 = 1.f + ex2(fminf(-LOG2E * g1, 60.f));
                        const float r = rcp(e0 * e1);
                        pk[m] = pack2(g0 * d[NT - 1][o] * (e1 * r), g1 * d[NT - 1][o + 1] * (e0 * r));
                    }
                    stg128(dst + h * 1024 + (((c * 4 + t) ^ g) << 4), make_uint4(pk[0], pk[1], pk[2], pk[3]));
                }
            }
            TS(WG * 128, j, WG * 4 + 2);
            __syncwarp();
            const uint32_t z = nbar_any(NB_WG0 + WG, 128, ld_rlx((const uint32_t*)(dst + (t & 1) * 1024)) & P.zero);
            const int f0 = idx * 128 + WG * 64, kg = (f0 + (tid & 1) * 63) / 928;
            if ((tid & 127) == 0 || ((tid & 127) == 1 && kg * 928 > f0)) red_add_u32(g_flag[F_H + kg][j], z + 1);
            TS(WG * 128, j, WG * 4 + 3);
        } else {
            uint8_t* dst = g_part[ST & 1] + (((use & (RING - 1)) * 64 + g) * 5 + idx / 3) * 1152 + ((idx % 3) * 3 + WG) * 128 + warp * 32 + t * 8;
            const uint32_t tag = ((use / RING) & 1) ^ 1, tm = ~t & 1;
#pragma unroll
            for (int m = 0; m < 8; m++) {
#pragma unroll
                for (int T = 0; T < NT; T++)
                    st_rlx64(dst + T * 256 + m * (8 * 5760), tagged(movm(pack2(d[T][4 * m], d[T][4 * m + 1])), tm, tag), movm(pack2(d[T][4 * m + 2], d[T][4 * m + 3])));
            }
            warp_arrive(bars + B_PUB * 8);
            TS(WG * 128, j, WG * 4 + 2);
        }
    }
}

template <int ST>
__device__ __forceinline__ void stage_producer(const Params& P, uint32_t sb, int idx) {
    using M = StageMap<ST>;
    const uint32_t bars = sb + SM_BAR;
    const int lane = threadIdx.x & 31;
    const int kg = ST == ST_F1 ? 0 : idx / 3;
    {
        const CUtensorMap* tm0 = ST == ST_WO ? &P.tmWo : ST == ST_F2 ? &P.tmW2 : &P.tmW1;
        const CUtensorMap* tm1 = ST == ST_F1 ? &P.tmW3 : tm0;
        const int k0 = kg * M::NKS, g0 = ST == ST_F1 ? idx * 2 : (idx % 3) * 3;
        if (ST != ST_WO) spin_cycles(G_DELAY);
        if (lane == 0) mbar_expect(bars + B_WL * 8, (M::NR0 + M::NR1) * 2048);
        __syncwarp();
#pragma unroll 1
        for (int ks = lane; ks < M::NKS; ks += 32) {
            if (is_rs(ks, M::NR0, M::NKS)) tma_w(sb + rs_idx(ks, M::NR0, M::NKS) * 2048, tm0, k0 + ks, g0, bars + B_WL * 8);
            else tma_w_prefetch(tm0, k0 + ks, g0);
            if (is_rs(ks, M::NR1, M::NKS)) tma_w(sb + (M::NR0 + rs_idx(ks, M::NR1, M::NKS)) * 2048, tm0, k0 + ks, g0 + 1, bars + B_WL * 8);
            else tma_w_prefetch(tm0, k0 + ks, g0 + 1);
            tma_w_prefetch(tm1, k0 + ks, ST == ST_F1 ? g0 : g0 + 2);
            if (ST == ST_F1) tma_w_prefetch(tm1, k0 + ks, g0 + 1);
        }
        nbar_sync(NB_ALL, 288);
        if (lane == 0) { fence_async_smem(); mbar_expect(bars + B_WS * 8, M::RNG); }
        __syncwarp();
#pragma unroll 1
        for (int ks = lane; ks < M::NKS; ks += 32) {
            if (!is_rs(ks, M::NR0, M::NKS)) tma_w(sb + M::W0A + (ks - rs_idx(ks, M::NR0, M::NKS)) * 2048, tm0, k0 + ks, g0, bars + B_WS * 8);
            if (!is_rs(ks, M::NR1, M::NKS)) tma_w(sb + M::W1A + (ks - rs_idx(ks, M::NR1, M::NKS)) * 2048, tm0, k0 + ks, g0 + 1, bars + B_WS * 8);
            tma_w(sb + M::W0B + ks * 2048, tm1, k0 + ks, ST == ST_F1 ? g0 : g0 + 2, bars + B_WS * 8);
            if (ST == ST_F1) tma_w(sb + M::W1B + ks * 2048, tm1, k0 + ks, g0 + 1, bars + B_WS * 8);
        }
    }
    if (lane != 0) return;
    const uint32_t e1 = lds32(sb + SM_EPOCH) + 1;
    const uint32_t target = e1 * (ST == ST_F1 ? 32 : ST == ST_WO ? (kg < 4 ? 14 : 12) : (kg < 4 ? 15 : 14));
    const int nch = M::NCH - (kg == 4);
    uint32_t s = 0, ph = 1;
#pragma unroll 1
    for (int j = 0; j < M::NIT; j++) {
        const int slot = j & (RING - 1);
        const uint8_t* src = ST == ST_F1 ? g_xf + slot * XIMG : ST == ST_WO ? g_o + (slot * 64 + kg * 13) * 8192 : g_h + (slot * FF + kg * 928) * 128;
        flag_poll(g_flag[ST == ST_F1 ? F_XF : (ST == ST_WO ? F_O : F_H) + kg][j], ST == ST_F1 && j > LAG && j < NSEG ? 2 * target : target);
        fence_acq_gpu();
        fence_async_glb();
        TS(256, j, 8);
#pragma unroll 1
        for (int c = 0; c < nch; c++) {
            const uint32_t bytes = (ST == ST_F2 && c == M::NCH - 1) ? 4096 : 8192;
            mbar_wait(bars + (B_EMPTY + s) * 8, ph);
            mbar_expect(bars + (B_FULL + s) * 8, bytes);
            bulk_g2s(sb + M::RNG + s * 8192, src + c * 8192, bytes, bars + (B_FULL + s) * 8);
            if (++s == M::NSLOT) { s = 0; ph ^= 1; }
        }
    }
}

template <int ST>
__device__ __forceinline__ void stage_split(const Params& P, uint32_t sb, int wg, int idx) {
    if (wg == 0) { reg_inc<240>(); stage_consumer<ST, 0>(P, sb, idx, 0); }
    else if (wg == 1) { reg_inc<240>(); stage_consumer<ST, 1>(P, sb, idx, 1); }
    else {
        reg_dec<24>();
        const int tid = fresh_tid();
        if (tid < 288) stage_producer<ST>(P, sb, idx);
        else if (tid == 288) {
#pragma unroll 1
            for (int j = 0; j < StageMap<ST>::NIT; j++) {
                mbar_wait(sb + SM_BAR + B_PUB * 8, j & 1);
                red_add_u32(g_flag[F_PW + ST][j], 1);
                TS(288, j, 9);
            }
        }
    }
}

#define NOG
__global__ void __cluster_dims__(2, 1, 1) __launch_bounds__(NTHREADS, 1) fused_kernel(const __grid_constant__ Params P) {
    extern __shared__ __align__(1024) uint8_t smem_raw[];
    const uint32_t sb = smem_u32(smem_raw);
    const int tid = threadIdx.x;
    const int wg = __shfl_sync(~0u, tid >> 7, 0);
    const int bid = blockIdx.x;
    if (tid == 0) {
        const uint32_t bars = sb + (bid < NENG ? E_BAR : SM_BAR);
        if ((sb & 0xffffff) != SM_BASE) __trap();
        TV(0, 126, 0, gtl()); TS(0, 126, 1);
        sts32(bars + 504, 0x1044); sts32(bars + 508, 0x3244);
        sts32(bars + 384, *(volatile uint32_t*)&g_epoch);
        for (int i = 0; i < 11; i++) mbar_init(bars + i * 8, 1);
        mbar_init(bars + B_QK * 8, 8); mbar_init(bars + B_V * 8, 4); mbar_init(bars + B_OM * 8, 4);
        mbar_init(bars + B_E01 * 8, 8); mbar_init(bars + B_TF * 8, 24);
        for (int i = 0; i < 8; i++) mbar_init(bars + (B_EMPTY + i) * 8, 8);
        mbar_init(bars + B_PUB * 8, 8);
        if (bid < NENG) { mbar_init(bars + B_RF * 8, 8); mbar_init(bars + B_PD * 8, 12); mbar_init(bars + B_MF * 8, 8); mbar_init(bars + B_M * 8, 4); }
        for (int i = 0; i < 14; i++) mbar_init(bars + (B_R9 + i) * 8, 1);
        asm volatile("fence.mbarrier_init.release.cluster;" ::: "memory");
    }
    __syncthreads();
    if (bid < NENG) {
        if (wg == 0) { reg_inc<240>(); engine_a(P, sb); }
        else if (wg == 1) { reg_inc<200>(); engine_b(P, sb); }
        else { reg_dec<64>(); engine_c(P, sb); }
        TV(0, 126, 2, gtl()); TS(0, 126, 3);
        cluster_sync_all();
    } else if (bid < CTA_WO) {
        const int idx = bid - CTA_F1;
        if (wg < 2) { NOG; reg_inc<92 + 4 * F1_NR>(); stage_consumer<ST_F1, 0>(P, sb, idx, wg); }
        else {
            reg_dec<504 - 2 * (92 + 4 * F1_NR)>();
            const int w = __shfl_sync(~0u, (fresh_tid() >> 5) & 3, 0);
            if (w == 0) {
                NOG;
                stage_producer<ST_F1>(P, sb, idx);
            } else {
                if ((tid & 31) == 0) red_add_u32(g_flag[F_DONE][0], 1);
                ln_first(P, (w - 1) * NF1 + idx, LN0_SPLIT, 3 * NF1);
                if (idx < 32) {
                    const uint32_t epoch = __shfl_sync(~0u, lds32(sb + SM_EPOCH), 0);
                    uint32_t ph = 0;
#pragma unroll 1
                    for (int j = w == 3 ? LAG : 0; j < (w == 3 ? NSEG : NSTEP + w - 1); j++) {
                        if (w == 3) mbar_wait(sb + SM_BAR + B_R9 * 8, (j - LAG) & 1);
                        ln_job(P, w == 2, j, w == 3 || j >= NSEG, idx, epoch, sb + StageMap<ST_F1>::ROWS + (w - 1) * 6912, sb + SM_BAR + (B_R9 + w) * 8, ph);
                        if (w == 1 && j >= LAG && elect()) mbar_arrive(sb + SM_BAR + B_R9 * 8);
                    }
                    TV(320, 126, 2, gtl());
                }
                return;
            }
        }
    } else if (bid < CTA_SP) {
NOG;
        if (bid < CTA_F2) stage_split<ST_WO>(P, sb, wg, bid - CTA_WO);
        else stage_split<ST_F2>(P, sb, wg, bid - CTA_F2);
    } else {
        const int w = (bid - CTA_SP) * 12 + (tid >> 5);
        ln_first(P, LN0_SPLIT + w, S_TOK, 24);
        const uint32_t e1 = lds32(sb + SM_EPOCH) + 1;
        uint32_t ph = 0;
#pragma unroll 1
        for (int item = (LAG + 1) * 32 + w; item < NSEG * 32; item += 24) {
            ln_job(P, 1, item >> 5, 1, item & 31, e1 - 1, sb + (tid >> 5) * 6912, sb + SM_BAR + (B_R9 + (tid >> 5)) * 8, ph);
        }
        TV(0, 126, 2, gtl()); TS(0, 126, 3);
        if (w == 23 && (tid & 31) == 0) {
            int n = 0;
            while ((int)(ld_rlx(g_flag[F_DONE][0]) - e1 * (CTA_SP * 12)) < 0) { SPIN_CHECK(n, 8); }
        }
        return;
    }
    __syncwarp();
    if ((fresh_tid() & 31) == 0) red_add_u32(g_flag[F_DONE][0], 1);
}

typedef CUresult (*EncodeFn)(CUtensorMap*, CUtensorMapDataType, cuuint32_t, void*, const cuuint64_t*, const cuuint64_t*,
                             const cuuint32_t*, const cuuint32_t*, CUtensorMapInterleave, CUtensorMapSwizzle,
                             CUtensorMapL2promotion, CUtensorMapFloatOOBfill);

void make_map(EncodeFn enc, CUtensorMap* m, const void* p, int rows, int cols) {
    cuuint64_t dims[3] = {64, (cuuint64_t)rows, (cuuint64_t)(cols / 64)};
    cuuint64_t strides[2] = {(cuuint64_t)cols * 2, 128};
    cuuint32_t box[3] = {64, 16, 1};
    cuuint32_t es[3] = {1, 1, 1};
    enc(m, CU_TENSOR_MAP_DATA_TYPE_BFLOAT16, 3, (void*)p, dims, strides, box, es, CU_TENSOR_MAP_INTERLEAVE_NONE,
        CU_TENSOR_MAP_SWIZZLE_128B, CU_TENSOR_MAP_L2_PROMOTION_L2_128B, CU_TENSOR_MAP_FLOAT_OOB_FILL_NONE);
}

void make_map2(EncodeFn enc, CUtensorMap* m, void* p, int words, int rows, int bw, int br) {
    cuuint64_t dims[2] = {(cuuint64_t)words, (cuuint64_t)rows};
    cuuint64_t strides[1] = {(cuuint64_t)words * 4};
    cuuint32_t box[2] = {(cuuint32_t)bw, (cuuint32_t)br};
    cuuint32_t es[2] = {1, 1};
    enc(m, CU_TENSOR_MAP_DATA_TYPE_UINT32, 2, p, dims, strides, box, es, CU_TENSOR_MAP_INTERLEAVE_NONE,
        CU_TENSOR_MAP_SWIZZLE_NONE, CU_TENSOR_MAP_L2_PROMOTION_NONE, CU_TENSOR_MAP_FLOAT_OOB_FILL_NONE);
}

}

extern "C" void kernel_launch(void* const* d_in, const int* in_sizes, int n_in, void* d_out, int out_size) {
    (void)in_sizes; (void)n_in; (void)out_size;
    static EncodeFn enc = nullptr;
    static void* rs = nullptr;
    if (!enc) {
        void* fn = nullptr;
        cudaDriverEntryPointQueryResult qr;
        cudaGetDriverEntryPoint("cuTensorMapEncodeTiled", &fn, cudaEnableDefault, &qr);
        enc = (EncodeFn)fn;
        cudaGetSymbolAddress(&rs, g_rs);
        cudaFuncSetAttribute(fused_kernel, cudaFuncAttributeMaxDynamicSharedMemorySize, SM_TOTAL);
    }
    Params P;
    make_map(enc, &P.tmWq, d_in[2], DM, 4096);
    make_map(enc, &P.tmWk, d_in[3], DM, 4096);
    make_map(enc, &P.tmWv, d_in[4], DM, 4096);
    make_map(enc, &P.tmWo, d_in[5], 4096, DM);
    make_map(enc, &P.tmW1, d_in[8], DM, FF);
    make_map(enc, &P.tmW3, d_in[9], DM, FF);
    make_map(enc, &P.tmW2, d_in[10], FF, DM);
    make_map2(enc, &P.tmRs, rs, 5120, 64, 16, 32);
    make_map2(enc, &P.tmR9, rs, 2560, 128, 4, 64);
    P.d128 = mkdesc(0, 1024, 1024, 1);
    P.d64 = mkdesc(0, 16, 512, 2);
    P.dX[0] = P.dX[1] = P.dX[2] = P.dX[3] = P.d128;
    P.dXk = P.dWk = P.d128 + E_WK / 16;
    P.dWo = P.d128 + E_WO / 16;
    P.dMq = P.dMk = P.dMv = mkdesc(E_MEM, 128, 1024, 0);
    P.dOm = mkdesc(E_OM, 16, 2048, 1);
    P.dQ = mkdesc(E_QX, 128, TG, 0);
    P.dK = mkdesc(E_KX, 128, 2 * TG, 0);
    P.zero = 0;
    P.x = (const bf16*)d_in[0];
    P.mem0 = (const bf16*)d_in[1];
    P.out = (bf16*)d_out;
    fused_kernel<<<NGRID, NTHREADS, SM_TOTAL>>>(P);
}
```

```cpp
#include <cuda_runtime.h>
#include <cuda_bf16.h>
#include <cuda.h>
#include <stdint.h>

typedef __nv_bfloat16 bf16;

namespace {

constexpr int S_TOK = 2048, DM = 576, NH = 32, FF = 4608, NSEG = 64;
#define LAG 7
#define RING 8
static_assert(RING > LAG && (RING & (RING - 1)) == 0, "ring slots are only protected by the dataflow cycle");
constexpr int NSTEP = NSEG + LAG;
constexpr int NENG = 64, NF1 = 36, NWO = 15, NF2 = 15, NGRID = 132;
constexpr int CTA_F1 = NENG, CTA_WO = CTA_F1 + NF1, CTA_F2 = CTA_WO + NWO, CTA_SP = CTA_F2 + NF2;
constexpr int NTHREADS = 384;
constexpr int XIMG = 9 * 8192;
constexpr int LN0_SPLIT = 1088;
#define RS_DELAY 600
#define RS_SKEW 60
#define RS_DELAY0 200
#define AG_DELAY 450
#define GB1 2
#define GB2 (4 - GB1)
#define GB3 2
#define LATE_WAIT 700
#define LATE_MUL 7
#define X7_DELAY 0
#define F1_NR 29
#define F1_SLOTS 4
#define CFENCE fence_async_smem()
#define KLOOP 3
#define LATE_NS 900
#define B_EARLY 1
#define S0Q 8
#define S0V 35
#define XS 0
#define XSEQ W(0) Q(0) Q(1) K(0) K(1) C W(2) B(2) E B(3) C W(4) B(4) M W(5) B(5) B(6) C W(7) B(7) T K(8) C Q(8) C
#define KEARLY 1
#define PROMO CU_TENSOR_MAP_L2_PROMOTION_L2_128B
#define G_DELAY 12000
#define WO_DELAY 3000
#define WO_PACE 0
#define F1_PACE 500
#define F2_PACE 500
constexpr int SPIN_LIMIT = 4000000;

enum { F_XE = 0, F_XF, F_PW, F_PF, F_O, F_H = F_O + 5, F_DONE = F_H + 5, F_COUNT };
__device__ uint32_t g_flag[F_COUNT][NSTEP + 2][8];
__device__ uint32_t g_epoch;
__device__ unsigned long long g_latest;
__device__ __align__(1024) uint8_t g_xe[NSTEP * XIMG];
__device__ __align__(1024) uint8_t g_xf[RING * XIMG];
__device__ __align__(1024) uint8_t g_o[RING * 64 * 8192];
__device__ __align__(1024) uint8_t g_h[RING * FF * 128];
__device__ __align__(1024) uint8_t g_part[2][RING * 64 * 5 * 1152];
__device__ __align__(1024) uint8_t g_x1[RING * 64 * 1152];
__device__ __align__(1024) uint8_t g_res[2][S_TOK * 1152];
__device__ __align__(1024) uint8_t g_rs[2 * NENG * 10240];
__device__ __align__(1024) uint8_t g_ag[2 * 18432];

struct Params {
    CUtensorMap tmWq, tmWk, tmWv, tmWo, tmW1, tmW3, tmW2, tmRs, tmR9;
    uint64_t d128, d64, dOm, dQ, dK, dX[6], dXk, dMq, dMq2, dMk, dMv, dWk, dWo;
    uint32_t zero;
    const bf16* x;
    const bf16* mem0;
    bf16* out;
};

constexpr int SM_TOTAL = 232448;
constexpr int SM_BAR = SM_TOTAL - 512;
constexpr int KRQ = 34, KRV = 35;
constexpr int E_WK = 0;
constexpr int E_WO = E_WK + 36 * 2048;
constexpr int E_WQ = E_WO + 36 * 2048;
constexpr int E_WV = E_WQ + (36 - KRQ) * 2048;
constexpr int E_RING = E_WV + (36 - KRV) * 2048;
constexpr int E_MEM = E_RING + 2 * 8192;
constexpr int E_OM = E_MEM + 18432;
constexpr int TG = 2064;
constexpr int E_T = E_OM + 4096;
constexpr int E_QX = E_T, E_QM = E_T, E_KX = E_T + 3 * TG, E_KM = E_T + 11 * TG, E_VX = E_T + 8 * TG, E_VM = E_T + 13 * TG;
constexpr int E_RS = E_T + 16384;
constexpr int E_BAR = E_T + 15 * TG;
constexpr int E_R2 = SM_TOTAL - 8192;
constexpr int SG = 1056, E_OUT = SM_TOTAL - 7 * SG - 1024;
static_assert(E_BAR + 512 <= E_OUT && E_RING % 1024 == 0 && E_MEM % 1024 == 0 && E_OM % 1024 == 0 && E_T % 1024 == 0 && E_R2 % 1024 == 0, "engine smem");
constexpr int E_ST1 = 19;
__host__ __device__ constexpr int e_stage(int j) { return j < 34 ? E_RING + j * 2048 : E_R2 + (j - 34) * 2048; }
static_assert(E_RING + 34 * 2048 <= E_BAR && 2 * E_ST1 <= 38, "staging");
__host__ __device__ constexpr int x_slot(int c) {
    return c < 2 ? E_RING + c * 8192 : c < 4 ? E_MEM + (c - 2) * 8192 : c == 4 ? E_R2 : c < 7 ? E_T + (c - 5) * 8192 : E_RING + (c - 7) * 8192;
}
enum { B_XF = 0, B_WL = 9, B_WS, B_QK, B_V, B_OM, B_E01, B_TF, B_RF = 1, B_PD = 3, B_MF = 6, B_M = 8, B_R9 = 49, B_RS = B_R9 + 2, B_ML = B_RS + 4, B_WO, B_FULL = 0, B_EMPTY = 16, B_PUB = 32 };
enum { NB_ALL = 1, NB_QKI, NB_SI, NB_PVI, NB_WIA, NB_WIB, NB_XI, NB_C, NB_WG0, NB_WG1 };
constexpr int SM_EPOCH = SM_BAR + 384, E_EPOCH = E_BAR + 384, E_ONE = E_BAR + 388, E_INV = E_BAR + 464, E_REDO = E_BAR + 528;

#define SPIN_CHECK(n, code) asm volatile("{.reg .pred p; setp.gt.s32 p, %0, %1; @p st.global.u32 [%2], %0;}" :: "r"(++(n)), "n"(SPIN_LIMIT), "l"(0ull))

#define EV(thr, k, v)
#define ES(thr, k)
#define EFLUSH(step)
#define TS(thr, step, k)
#define TV(thr, step, k, v)

__device__ __forceinline__ uint32_t smem_u32(const void* p) { return (uint32_t)__cvta_generic_to_shared(p); }
__device__ __forceinline__ uint32_t mapa(uint32_t a, uint32_t r) {
    uint32_t o; asm("mapa.shared::cluster.u32 %0, %1, %2;" : "=r"(o) : "r"(a), "r"(r)); return o;
}
__device__ __forceinline__ void mbar_init(uint32_t b, uint32_t cnt) {
    asm volatile("mbarrier.init.shared::cta.b64 [%0], %1;" :: "r"(b), "r"(cnt) : "memory");
}
__device__ __forceinline__ void mbar_arrive(uint32_t b) {
    asm volatile("mbarrier.arrive.shared::cta.b64 _, [%0];" :: "r"(b) : "memory");
}
__device__ __forceinline__ void mbar_arrive_remote(uint32_t b) {
    asm volatile("mbarrier.arrive.relaxed.cluster.shared::cluster.b64 _, [%0];" :: "r"(b) : "memory");
}
__device__ __forceinline__ void mbar_expect(uint32_t b, uint32_t bytes) {
    asm volatile("mbarrier.arrive.expect_tx.shared::cta.b64 _, [%0], %1;" :: "r"(b), "r"(bytes) : "memory");
}
#define RETRY(n, code) n = 1
#define MBAR_WAIT(SEM) asm volatile("{.reg .pred p; W: mbarrier.try_wait.parity" SEM ".shared::cta.b64 p, [%0], %1; @!p bra W;}" :: "r"(b), "r"(par) : "memory")
__device__ __forceinline__ void mbar_wait(uint32_t b, uint32_t par) { MBAR_WAIT(""); }
__device__ __forceinline__ void mbar_wait_cl(uint32_t b, uint32_t par) {
    MBAR_WAIT(".relaxed.cluster");
    asm volatile("fence.acquire.sync_restrict::shared::cluster.cluster;" ::: "memory");
}
__device__ __forceinline__ void nbar_sync(int id, int n) { asm volatile("bar.sync %0, %1;" :: "r"(id), "r"(n) : "memory"); }
__device__ __forceinline__ void nbar_arrive(int id, int n) { asm volatile("bar.arrive %0, %1;" :: "r"(id), "r"(n) : "memory"); }
__device__ __forceinline__ uint32_t nbar_any(int id, int n, uint32_t v) {
    uint32_t r;
    asm volatile("{.reg .pred p, q; setp.ne.u32 p, %3, 0; bar.red.or.pred q, %1, %2, p; selp.u32 %0, 1, 0, q;}" : "=r"(r) : "r"(id), "r"(n), "r"(v) : "memory");
    return r;
}
__device__ __forceinline__ uint32_t clock_after(uint32_t zero) {
    uint32_t t;
    asm volatile("{.reg .pred p; setp.eq.u32 p, %1, 0; mov.u32 %0, 0; @p mov.u32 %0, %%clock;}" : "=r"(t) : "r"(zero) : "memory");
    return t;
}
__device__ __forceinline__ void cluster_sync_all() {
    asm volatile("barrier.cluster.arrive.release.aligned; barrier.cluster.wait.acquire.aligned;" ::: "memory");
}
__device__ __forceinline__ void cluster_arrive() { asm volatile("barrier.cluster.arrive.relaxed.aligned;" ::: "memory"); }
__device__ __forceinline__ void cluster_wait() { asm volatile("barrier.cluster.wait.aligned;" ::: "memory"); }
__device__ __forceinline__ void fence_async_smem() { asm volatile("fence.proxy.async.shared::cta;" ::: "memory"); }
__device__ __forceinline__ void fence_async_glb() { asm volatile("fence.proxy.async.global;" ::: "memory"); }
__device__ __forceinline__ void fence_rel_gpu() { asm volatile("fence.release.gpu;" ::: "memory"); }
__device__ __forceinline__ void fence_acq_gpu() { asm volatile("fence.acquire.gpu;" ::: "memory"); }
__device__ __forceinline__ int fresh_tid() { int t; asm volatile("mov.u32 %0, %%tid.x;" : "=r"(t)); return t; }
__device__ __forceinline__ int fresh_bid() { int t; asm volatile("mov.u32 %0, %%ctaid.x;" : "=r"(t)); return t; }
__device__ __forceinline__ uint32_t keep(uint32_t v) { asm volatile("" : "+r"(v)); return v; }
__device__ __forceinline__ uint32_t opaque(uint32_t v) { return __shfl_xor_sync(~0u, v, 0); }
__device__ __forceinline__ bool elect() {
    uint32_t p; asm volatile("{.reg .pred p; elect.sync _|p, 0xffffffff; selp.u32 %0, 1, 0, p;}" : "=r"(p)); return p;
}
__device__ __forceinline__ uint32_t clock32() { uint32_t t; asm volatile("mov.u32 %0, %%clock;" : "=r"(t) :: "memory"); return t; }
__device__ __forceinline__ void red_add_u32(uint32_t* p, uint32_t v) {
    asm volatile("red.relaxed.gpu.global.add.u32 [%0], %1;" :: "l"(p), "r"(v) : "memory");
}
__device__ __forceinline__ uint32_t ld_rlx(const uint32_t* p) {
    uint32_t v; asm volatile("ld.relaxed.gpu.global.u32 %0, [%1];" : "=r"(v) : "l"(p) : "memory"); return v;
}
__device__ __forceinline__ void st_rlx128(void* p, uint4 v) {
    asm volatile("{.reg .b128 r; .reg .b64 a, b; mov.b64 a, {%1,%2}; mov.b64 b, {%3,%4}; mov.b128 r, {a, b}; st.relaxed.gpu.global.b128 [%0], r;}"
                 :: "l"(p), "r"(v.x), "r"(v.y), "r"(v.z), "r"(v.w) : "memory");
}
__device__ __forceinline__ void st_rlx64(void* p, uint32_t a, uint32_t b) {
    asm volatile("{.reg .b64 r; mov.b64 r, {%1,%2}; st.relaxed.gpu.global.b64 [%0], r;}" :: "l"(p), "r"(a), "r"(b) : "memory");
}
__device__ __forceinline__ void st_rlx32(void* p, uint32_t v) { asm volatile("st.relaxed.gpu.global.u32 [%0], %1;" :: "l"(p), "r"(v) : "memory"); }
__device__ __forceinline__ uint32_t xor_or(uint32_t a, uint32_t b, uint32_t t) {
    uint32_t d; asm("lop3.b32 %0, %1, %2, %3, 0x7E;" : "=r"(d) : "r"(a), "r"(b), "r"(t)); return d;
}
__device__ __forceinline__ uint32_t tagged(uint32_t w, uint32_t m, uint32_t tag) {
    uint32_t d; asm("lop3.b32 %0, %1, %2, %3, 0xB8;" : "=r"(d) : "r"(w), "r"(m), "r"(tag)); return d;
}
__device__ __forceinline__ uint32_t or3(uint32_t a, uint32_t b, uint32_t c) {
    uint32_t d; asm("lop3.b32 %0, %1, %2, %3, 0xFE;" : "=r"(d) : "r"(a), "r"(b), "r"(c)); return d;
}
__device__ __forceinline__ uint32_t or_bit0(uint32_t a, uint32_t b) {
    uint32_t d; asm("lop3.b32 %0, %1, %2, 1, 0xA8;" : "=r"(d) : "r"(a), "r"(b)); return d;
}
__device__ __forceinline__ uint4 ld_l2_128(const void* p) {
    uint4 v;
    asm volatile("ld.relaxed.gpu.global.v4.u32 {%0,%1,%2,%3}, [%4];" : "=r"(v.x), "=r"(v.y), "=r"(v.z), "=r"(v.w) : "l"(p) : "memory");
    return v;
}
__device__ __forceinline__ void stg128(void* p, uint4 v) {
    asm volatile("st.global.v4.b32 [%0], {%1,%2,%3,%4};" :: "l"(p), "r"(v.x), "r"(v.y), "r"(v.z), "r"(v.w) : "memory");
}
__device__ __forceinline__ void stg64(void* p, uint32_t a, uint32_t b) {
    asm volatile("st.global.v2.b32 [%0], {%1,%2};" :: "l"(p), "r"(a), "r"(b) : "memory");
}
__device__ __forceinline__ void st_async128(uint32_t a, uint4 v, uint32_t mb) {
    asm volatile("st.async.shared::cluster.mbarrier::complete_tx::bytes.v4.b32 [%0], {%1,%2,%3,%4}, [%5];"
                 :: "r"(a), "r"(v.x), "r"(v.y), "r"(v.z), "r"(v.w), "r"(mb) : "memory");
}
__device__ __forceinline__ void st_async32(uint32_t a, uint32_t v, uint32_t mb) {
    asm volatile("st.async.shared::cluster.mbarrier::complete_tx::bytes.b32 [%0], %1, [%2];" :: "r"(a), "r"(v), "r"(mb) : "memory");
}
__device__ __forceinline__ void sts128(uint32_t a, uint4 v) {
    asm volatile("st.shared.v4.b32 [%0], {%1,%2,%3,%4};" :: "r"(a), "r"(v.x), "r"(v.y), "r"(v.z), "r"(v.w) : "memory");
}
__device__ __forceinline__ void sts32(uint32_t a, uint32_t v) { asm volatile("st.shared.b32 [%0], %1;" :: "r"(a), "r"(v) : "memory"); }
__device__ __forceinline__ uint32_t lds32(uint32_t a) { uint32_t v; asm volatile("ld.shared.b32 %0, [%1];" : "=r"(v) : "r"(a) : "memory"); return v; }
__device__ __forceinline__ uint2 lds64(uint32_t a) {
    uint2 v; asm volatile("ld.shared.v2.b32 {%0,%1}, [%2];" : "=r"(v.x), "=r"(v.y) : "r"(a) : "memory"); return v;
}
__device__ __forceinline__ uint4 lds128(uint32_t a) {
    uint4 v; asm volatile("ld.shared.v4.b32 {%0,%1,%2,%3}, [%4];" : "=r"(v.x), "=r"(v.y), "=r"(v.z), "=r"(v.w) : "r"(a) : "memory"); return v;
}
__device__ __forceinline__ void bulk_g2s(uint32_t dst, const void* src, uint32_t bytes, uint32_t mb) {
    asm volatile("cp.async.bulk.shared::cluster.global.mbarrier::complete_tx::bytes [%0], [%1], %2, [%3];"
                 :: "r"(dst), "l"(src), "r"(bytes), "r"(mb) : "memory");
}
__device__ __forceinline__ void bulk_s2peer(uint32_t dst, uint32_t src, uint32_t bytes, uint32_t mb) {
    asm volatile("cp.async.bulk.shared::cluster.shared::cta.mbarrier::complete_tx::bytes [%0], [%1], %2, [%3];"
                 :: "r"(dst), "r"(src), "r"(bytes), "r"(mb) : "memory");
}
__device__ __forceinline__ void tma_2d(uint32_t dst, const CUtensorMap* tm, int x, int y, uint32_t mb) {
    asm volatile("cp.async.bulk.tensor.2d.shared::cluster.global.mbarrier::complete_tx::bytes [%0], [%1, {%2,%3}], [%4];"
                 :: "r"(dst), "l"(tm), "r"(x), "r"(y), "r"(mb) : "memory");
}
__device__ __forceinline__ void tma_w(uint32_t dst, const CUtensorMap* tm, int ks, int grp, uint32_t mb) {
    asm volatile("cp.async.bulk.tensor.3d.shared::cluster.global.mbarrier::complete_tx::bytes [%0], [%1, {%2,%3,%4}], [%5];"
                 :: "r"(dst), "l"(tm), "r"(0), "r"(ks * 16), "r"(grp), "r"(mb) : "memory");
}
__device__ __forceinline__ void ldsm4t(uint32_t* r, uint32_t a) {
    asm volatile("ldmatrix.sync.aligned.m8n8.x4.trans.shared.b16 {%0,%1,%2,%3}, [%4];"
                 : "=r"(r[0]), "=r"(r[1]), "=r"(r[2]), "=r"(r[3]) : "r"(a) : "memory");
}
__device__ __forceinline__ uint32_t movm(uint32_t a) {
    uint32_t d; asm volatile("movmatrix.sync.aligned.m8n8.trans.b16 %0, %1;" : "=r"(d) : "r"(a)); return d;
}
__device__ __forceinline__ uint32_t pack2(float lo, float hi) {
    uint32_t d; asm("cvt.rn.bf16x2.f32 %0, %1, %2;" : "=r"(d) : "f"(hi), "f"(lo)); return d;
}
__device__ __forceinline__ float bf_lo(uint32_t w) { return __uint_as_float(w << 16); }
__device__ __forceinline__ float bf_hi(uint32_t w) { return __uint_as_float(w & 0xffff0000u); }
__device__ __forceinline__ float ex2(float x) { float y; asm("ex2.approx.ftz.f32 %0, %1;" : "=f"(y) : "f"(x)); return y; }
__device__ __forceinline__ float rcp(float x) { float y; asm("rcp.approx.ftz.f32 %0, %1;" : "=f"(y) : "f"(x)); return y; }
__device__ __forceinline__ void spin_cycles(int c) {
    uint32_t t0, t1;
    asm volatile("mov.u32 %0, %%clock;" : "=r"(t0));
    do { asm volatile("mov.u32 %0, %%clock;" : "=r"(t1)); } while ((int)(t1 - t0) < c);
}
template <int N> __device__ __forceinline__ void reg_inc() { asm volatile("setmaxnreg.inc.sync.aligned.u32 %0;" :: "n"(N)); }
template <int N> __device__ __forceinline__ void reg_dec() { asm volatile("setmaxnreg.dec.sync.aligned.u32 %0;" :: "n"(N)); }

__device__ __forceinline__ void pin(const Params& P, uint32_t v) {
    asm volatile("{.reg .pred p; .reg .b32 t; and.b32 t, %0, %1; setp.ne.u32 p, t, 0; @p st.shared.u32 [%0], t;}" :: "r"(v), "r"(P.zero) : "memory");
    __syncwarp();
}
__device__ __forceinline__ void flag_poll(const uint32_t* f, uint32_t target) {
    int n = 0;
    while ((int)(ld_rlx(f) - target) < 0) {
        SPIN_CHECK(n, (int)(f - &g_flag[0][0][0]) / 8);
    }
}
__device__ __forceinline__ void flag_signal_after(const Params& P, uint32_t* f, uint32_t loaded) { red_add_u32(f, (loaded & P.zero) + 1); }
__device__ __forceinline__ void flag_signal(uint32_t* f) {
    fence_rel_gpu();
    red_add_u32(f, 1);
}

constexpr uint32_t SM_BASE = 1024;
__host__ __device__ constexpr uint64_t mkdesc(uint32_t off, uint32_t lbo, uint32_t sbo, uint32_t swz) {
    return (uint64_t)((SM_BASE + off) >> 4) | ((uint64_t)(lbo >> 4) << 16) | ((uint64_t)(sbo >> 4) << 32) | ((uint64_t)swz << 62);
}
__device__ __forceinline__ void dmove(uint64_t& d, int delta) { asm volatile("add.s64 %0, %0, %1;" : "+l"(d) : "l"((long long)delta)); }
__device__ __forceinline__ void wg_fence() { asm volatile("wgmma.fence.sync.aligned;" ::: "memory"); }
__device__ __forceinline__ void wg_commit() { asm volatile("wgmma.commit_group.sync.aligned;" ::: "memory"); }
template <int N> __device__ __forceinline__ void wg_wait() { asm volatile("wgmma.wait_group.sync.aligned %0;" :: "n"(N) : "memory"); }

#define F4(c, d, o) c(d[o]), c(d[o + 1]), c(d[o + 2]), c(d[o + 3])
#define F8(c, d, o) F4(c, d, o), F4(c, d, o + 4)
#define F32(c, d, o) F8(c, d, o), F8(c, d, o + 8), F8(c, d, o + 16), F8(c, d, o + 24)
#define L8 "%0,%1,%2,%3,%4,%5,%6,%7"
#define L20 L8 ",%8,%9,%10,%11,%12,%13,%14,%15,%16,%17,%18,%19"
#define L32 L20 ",%20,%21,%22,%23,%24,%25,%26,%27,%28,%29,%30,%31"
#define L64 L32 ",%32,%33,%34,%35,%36,%37,%38,%39,%40,%41,%42,%43,%44,%45,%46,%47,%48,%49,%50,%51,%52,%53,%54,%55,%56,%57,%58,%59,%60,%61,%62,%63"
#define O8(c) F8(c, d, 0)
#define O20(c) F8(c, d, 0), F8(c, d, 8), F4(c, d, 16)
#define O32(c) F32(c, d, 0)
#define O64(c) F32(c, d, 0), F32(c, d, 32)
#define WG_BOTH(TXT_PRE, TXT_POST, OUTS, ...)                                                   \
    if (acc > 0) asm volatile(TXT_PRE "1" TXT_POST : OUTS("+f") : __VA_ARGS__);                 \
    else if (acc < 0) asm volatile(TXT_PRE "0" TXT_POST : OUTS("+f") : __VA_ARGS__);            \
    else asm volatile(TXT_PRE "0" TXT_POST : OUTS("=f") : __VA_ARGS__)
#define AREGS "r"(a[0]), "r"(a[1]), "r"(a[2]), "r"(a[3])
template <int TB> __device__ __forceinline__ void wg_rs16(float* d, const uint32_t* a, uint64_t db, int acc) {
    WG_BOTH("wgmma.mma_async.sync.aligned.m64n16k16.f32.bf16.bf16 {" L8 "}, {%8,%9,%10,%11}, %12, ", ", 1, 1, %13;", O8, AREGS, "l"(db), "n"(TB));
}
template <int TB> __device__ __forceinline__ void wg_ss16(float* d, uint64_t da, uint64_t db, int acc) {
    WG_BOTH("wgmma.mma_async.sync.aligned.m64n16k16.f32.bf16.bf16 {" L8 "}, %8, %9, ", ", 1, 1, 1, %10;", O8, "l"(da), "l"(db), "n"(TB));
}
template <int TB> __device__ __forceinline__ void wg_ss40(float* d, uint64_t da, uint64_t db, int acc) {
    WG_BOTH("wgmma.mma_async.sync.aligned.m64n40k16.f32.bf16.bf16 {" L20 "}, %20, %21, ", ", 1, 1, 1, %22;", O20, "l"(da), "l"(db), "n"(TB));
}
template <int TB> __device__ __forceinline__ void wg_rs64(float* d, const uint32_t* a, uint64_t db, int acc) {
    WG_BOTH("wgmma.mma_async.sync.aligned.m64n64k16.f32.bf16.bf16 {" L32 "}, {%32,%33,%34,%35}, %36, ", ", 1, 1, %37;", O32, AREGS, "l"(db), "n"(TB));
}
template <int TB> __device__ __forceinline__ void wg_ss64(float* d, uint64_t da, uint64_t db, int acc) {
    WG_BOTH("wgmma.mma_async.sync.aligned.m64n64k16.f32.bf16.bf16 {" L32 "}, %32, %33, ", ", 1, 1, 1, %34;", O32, "l"(da), "l"(db), "n"(TB));
}
template <int TB> __device__ __forceinline__ void wg_rs128(float* d, const uint32_t* a, uint64_t db, int acc) {
    WG_BOTH("wgmma.mma_async.sync.aligned.m64n128k16.f32.bf16.bf16 {" L64 "}, {%64,%65,%66,%67}, %68, ", ", 1, 1, %69;", O64, AREGS, "l"(db), "n"(TB));
}
__device__ __forceinline__ uint32_t frag_addr(uint32_t base) {
    const int tid = threadIdx.x, i = tid & 7, j = (tid >> 3) & 3, warp = (tid >> 5) & 3;
    return base + ((j >> 1) * 8 + i) * 128 + ((((warp << 1) + (j & 1)) ^ i) << 4);
}

constexpr float SM_SCALE = 0.08838834764831845f;
constexpr float LOG2E = 1.4426950408889634f;

__device__ __forceinline__ void add8(float* f, uint4 a) {
    f[0] += bf_lo(a.x); f[1] += bf_hi(a.x); f[2] += bf_lo(a.y); f[3] += bf_hi(a.y);
    f[4] += bf_lo(a.z); f[5] += bf_hi(a.z); f[6] += bf_lo(a.w); f[7] += bf_hi(a.w);
}
__device__ __forceinline__ void sum_row(uint4* xw, const uint8_t* part, const uint8_t* res, uint32_t tag, uint32_t buf, uint32_t mb, uint32_t& ph, int l) {
    int n = 0;
#pragma unroll 1
    while (true) {
        if (elect()) { mbar_expect(mb, 6 * 1152); bulk_g2s(buf, part, 5 * 1152, mb); bulk_g2s(buf + 5 * 1152, res, 1152, mb); }
        SPIN_CHECK(n, 7);
        mbar_wait(mb, ph);
        ph ^= 1;
        uint32_t bad = 0;
#pragma unroll
        for (int k = 0; k < 3; k++) {
            uint4 a[6];
#pragma unroll
            for (int j = 0; j < 6; j++) a[j] = lds128(buf + l * 16 + k * 384 + j * 1152);
            float f[8] = {0.f, 0.f, 0.f, 0.f, 0.f, 0.f, 0.f, 0.f};
#pragma unroll
            for (int j = 0; j < 6; j++) add8(f, a[j]);
            bad = or3(bad | (a[4].x ^ tag), xor_or(a[0].x, a[1].x, tag), xor_or(a[2].x, a[3].x, tag));
            xw[k] = make_uint4(pack2(f[0], f[1]), pack2(f[2], f[3]), pack2(f[4], f[5]), pack2(f[6], f[7]));
        }
        if (!__any_sync(~0u, bad & 1)) break;
    }
}
__device__ __forceinline__ void ln_row(const Params& P, const uint4* xw, uint8_t* keep_at, uint8_t* img, int n, uint32_t* flag, int lane) {
    const int l = lane < 24 ? lane : 0;
    const float shift = bf_lo(__shfl_sync(~0u, xw[0].x, 0));
    float s = 0.f, q = 0.f;
#pragma unroll
    for (int k = 0; k < 3; k++) {
        float f[8] = {-shift, -shift, -shift, -shift, -shift, -shift, -shift, -shift};
        add8(f, xw[k]);
#pragma unroll
        for (int j = 0; j < 8; j++) { s += f[j]; q += f[j] * f[j]; }
    }
    if (lane >= 24) s = q = 0.f;
#pragma unroll
    for (int o = 16; o; o >>= 1) { s += __shfl_xor_sync(~0u, s, o); q += __shfl_xor_sync(~0u, q, o); }
    const float mean = s * (1.f / DM);
    const float rstd = rsqrtf(fmaxf(q * (1.f / DM) - mean * mean, 0.f) + 1e-5f), mu = shift + mean;
    const int row = ((n >> 1) & 3) * 8 + ((n >> 3) & 3) * 2 + (n & 33);
    img += row * 128;
    if (lane < 24) {
        uint8_t* d = img + (l >> 3) * 8192 + (l & 1) * 8;
        const uint32_t c0 = ((l & 6) ^ (row & 7)) << 4;
#define NRM(w) pack2((bf_lo(w) - mu) * rstd, (bf_hi(w) - mu) * rstd)
#pragma unroll
        for (int k = 0; k < 3; k++) {
            stg64(d + k * 24576 + c0, NRM(xw[k].x), NRM(xw[k].z));
            stg64(d + k * 24576 + (c0 ^ 16), NRM(xw[k].y), NRM(xw[k].w));
        }
#undef NRM
#pragma unroll
        for (int k = 0; k < 3; k++) stg128(keep_at + l * 16 + k * 384, xw[k]);
    }
    __syncwarp();
    const int j = lane < 18 ? lane : 0;
    const uint32_t v = ld_rlx((const uint32_t*)(j < 9 ? img + j * 8192 : keep_at + (j - 9) * 128));
    if (lane == 0) flag_signal_after(P, flag, v);
}
__device__ __forceinline__ void ln_first(const Params& P, int row0, int row1, int stride) {
    const int lane = threadIdx.x & 31, l = lane < 24 ? lane : 0;
#pragma unroll 1
    for (int tok = row0; tok < row1; tok += stride) {
        const uint8_t* src = (const uint8_t*)P.x + tok * 1152 + (l >> 1) * 32 + (l & 1) * 8;
        uint4 xw[3];
#pragma unroll
        for (int k = 0; k < 3; k++) {
            const uint2 a = __ldg((const uint2*)(src + k * 384)), b = __ldg((const uint2*)(src + k * 384 + 16));
            xw[k] = make_uint4(a.x, b.x, a.y, b.y);
        }
        ln_row(P, xw, g_res[0] + tok * 1152, g_xe + (tok >> 5) * XIMG, tok & 31, g_flag[F_XE][tok >> 5], lane);
    }
}
__device__ __forceinline__ void ln_job(const Params& P, int second, int j, int late, int r, uint32_t epoch, uint32_t buf, uint32_t mb, uint32_t& ph) {
#define LAYER (late | (j >= NSEG))
#define TOK ((j - (late & second) - LAYER * LAG) * 32 + r)
#define ROUND (j + (late & ~second))
#define X1 (g_x1 + ((ROUND & (RING - 1)) * 64 + late * 32 + r) * 1152)
    uint4 xw[3];
    {
        const uint32_t use = epoch * NSTEP + j;
        const int lane = fresh_tid() & 31;
        flag_poll(g_flag[F_PW + second][j], (epoch + 1) * NWO);
        fence_acq_gpu();
        fence_async_glb();
        TS(288, j, 10); TS(320, j, 13);
        sum_row(xw, g_part[second] + ((use & (RING - 1)) * 64 + (second ? late : LAYER) * 32 + r) * 5760, second ? X1 : g_res[LAYER] + TOK * 1152,
                ((use / RING) & 1) ^ 1, buf, mb, ph, lane < 24 ? lane : 0);
        TS(288, j, 11); TS(320, j, 14);
    }
    j = keep(j);
    const int lane = fresh_tid() & 31, l = lane < 24 ? lane : 0;
    if (second && LAYER) {
        if (lane < 24) {
            uint8_t* d = (uint8_t*)P.out + TOK * 1152 + (l >> 1) * 32 + (l & 1) * 8;
#pragma unroll
            for (int k = 0; k < 3; k++) { stg64(d + k * 384, xw[k].x, xw[k].z); stg64(d + k * 384 + 16, xw[k].y, xw[k].w); }
        }
        if (lane == 0 && j + LAG + 1 < NSTEP) red_add_u32(g_flag[F_XE][j + LAG + 1], 1);
    } else {
        ln_row(P, xw, second ? g_res[1] + TOK * 1152 : X1, second ? g_xe + (j + LAG) * XIMG : g_xf + (ROUND & (RING - 1)) * XIMG,
               (second | late) * 32 + r, second ? g_flag[F_XE][j + LAG] : g_flag[F_XF][ROUND], lane);
    }
    TS(288, j, 12); TS(320, j, 15);
#undef X1
#undef ROUND
#undef TOK
#undef LAYER
}

template <int KR, int WG>
__device__ __forceinline__ void load_wregs(uint32_t (&w)[KR][4], uint32_t sb) {
    const uint32_t base = frag_addr(sb);
    mbar_wait(sb + E_BAR + B_WL * 8, 0);
    TV(0, 126, 4, gtl());
#pragma unroll
    for (int ks = 0; ks < E_ST1; ks++) ldsm4t(w[ks], base + e_stage(WG * E_ST1 + ks));
    nbar_sync(NB_ALL, NTHREADS);
    mbar_wait(sb + E_BAR + B_WL * 8, 1);
    TV(0, 126, 5, gtl());
#pragma unroll
    for (int ks = E_ST1; ks < KR; ks++) ldsm4t(w[ks], base + e_stage(WG * E_ST1 + ks - E_ST1));
    nbar_sync(NB_XI, 256);
    cluster_wait();
    TV(0, 126, 6, gtl());
    mbar_wait(sb + E_BAR + B_WS * 8, 0);
    TV(0, 126, 7, gtl());
}
__host__ __device__ constexpr int m_pos(int tile) { return tile == 8 ? 0 : 1 + 2 * (tile & 3) + (tile >> 2); }
__host__ __device__ constexpr int m_off(int ks) { return m_pos(ks >> 2) * 128 + (ks & 3) * 16; }
template <int KR> struct Res {
    static constexpr int NS = 36 - KR, S0 = KR == KRQ ? S0Q : S0V;
    __host__ __device__ static constexpr bool ss(int ks) { return ks >= S0 && ks < S0 + NS; }
    __host__ __device__ static constexpr int reg(int ks) { return ks < S0 ? ks : ks < S0 + NS ? 0 : ks - NS; }
    __host__ __device__ static constexpr int step(int r) { return r < S0 ? r : r + NS; }
};
template <int KR, bool LEAD>
__device__ __forceinline__ void proj_mem(uint64_t dw, float* d, const uint32_t (&w)[KR][4], uint32_t wss) {
    using R = Res<KR>;
    dw += m_off(R::step(0));
    wg_fence();
#pragma unroll
    for (int j = 0; j < R::NS; j++) wg_ss16<1>(d, mkdesc(wss + j * 2048, 1024, 1024, 1), mkdesc(E_MEM, 128, 1024, 0) + m_off(R::S0 + j), j > 0);
#pragma unroll
    for (int r = 0; r < KR; r++) { wg_rs16<1>(d, w[r], dw, 1); if (r < KR - 1) dmove(dw, m_off(R::step(r + 1)) - m_off(R::step(r))); }
    wg_commit();
    if (LEAD) nbar_arrive(NB_QKI, NTHREADS);
}
struct Walk {
    uint64_t d;
    int at = -1;
    __device__ __forceinline__ uint64_t to(uint64_t base, int off) {
        if (at < 0) d = base + off; else if (off != at) dmove(d, off - at);
        at = off;
        return d;
    }
};
template <int KR, int WHAT>
__device__ __forceinline__ void proj_x(const Params& P, Walk* wk, float* d, float* dk, const uint32_t (&w)[KR][4], uint32_t wss, int c) {
    using R = Res<KR>;
    const int n = (WHAT & 2) + (c >= 7);
#pragma unroll
    for (int kk = 0; kk < 4; kk++) {
        const int ks = c * 4 + kk;
        uint64_t dx = 0;
        if (WHAT != 1 || !R::ss(ks)) dx = wk[n].to(P.dX[n + (KR == KRQ ? 0 : 4)], x_slot(c) / 16 + kk * 2);
        if (WHAT & 2) wg_ss64<0>(dk, wk[4].to(P.dXk, m_pos(c) * 512 + kk * 128), dx, ks > 0);
        if ((WHAT & 1) && !R::ss(ks)) wg_rs64<0>(d, w[R::reg(ks)], dx, ks > 0);
        if ((WHAT & 1) && R::ss(ks)) wg_ss64<0>(d, mkdesc(wss + (ks - R::S0) * 2048, 1024, 1024, 1), mkdesc(x_slot(c) + kk * 32, 1024, 1024, 1), 1);
    }
}
__device__ __forceinline__ void x_wait(uint32_t sb, int c, uint32_t par) {
    if (c == 0 || c == 2 || c == 4 || c == 5 || c == 7) mbar_wait(sb + E_BAR + (B_XF + c) * 8, par);
    wg_fence();
}
template <bool VPERM> __device__ __forceinline__ uint32_t tile_row(int tid, int rank) {
    const int w = (tid >> 5) & 3, g = (tid >> 2) & 7;
    return (rank * 64 + (VPERM ? (w >> 1) * 32 + (g >> 1) * 8 + (w & 1) * 4 + (g & 1) : w * 16 + g)) * 16;
}
template <bool VPERM>
__device__ __forceinline__ void put_mem(const float* d, uint32_t a, int rank, uint32_t peer_off, uint32_t mb) {
    const uint32_t p0 = pack2(d[0], d[1]), p1 = pack2(d[2], d[3]), p2 = pack2(d[4], d[5]), p3 = pack2(d[6], d[7]);
    constexpr int R = VPERM ? 32 : 128;
    st_async32(a + peer_off, rank ? p0 : p2, mb + peer_off);
    st_async32(a + R + peer_off, rank ? p1 : p3, mb + peer_off);
    sts32(a, rank ? p2 : p0);
    sts32(a + R, rank ? p3 : p1);
}
#define XCOL(c) "r"(pack2(e[16 * c], e[16 * c + 1])), "r"(pack2(e[16 * c + 4], e[16 * c + 5])), "r"(pack2(e[16 * c + 8], e[16 * c + 9])), "r"(pack2(e[16 * c + 12], e[16 * c + 13]))
__device__ __forceinline__ void put_xv(const float* d, uint32_t a, int rank, uint32_t peer_off, uint32_t mb) {
    uint4 c[4];
#pragma unroll
    for (int j = 0; j < 4; j++) {
        const float* e = d + (j >> 1) * 16 + (j & 1) * 2;
        c[j] = make_uint4(pack2(e[0], e[1]), pack2(e[4], e[5]), pack2(e[8], e[9]), pack2(e[12], e[13]));
    }
    const uint32_t b = a + peer_off, m = keep(mb + peer_off);
    if (rank) { st_async128(b, c[0], m); st_async128(b + 32, c[1], m); sts128(a, c[2]); sts128(a + 32, c[3]); }
    else { st_async128(b, c[2], m); st_async128(b + 32, c[3], m); sts128(a, c[0]); sts128(a + 32, c[1]); }
}
__device__ __forceinline__ void park_x(const float* d, uint32_t a0, uint32_t a1) {
#pragma unroll
    for (int h = 0; h < 2; h++) {
        const float* e = d + 2 * h;
        asm volatile("st.shared.v4.b32 [%8], {%0,%1,%2,%3}; st.shared.v4.b32 [%9], {%4,%5,%6,%7};"
                     :: XCOL(0), XCOL(1), "r"(a0 + h * 128), "r"(a1 + h * 128) : "memory");
    }
}
#undef XCOL
__device__ __forceinline__ void warp_arrive(uint32_t b) { __syncwarp(); if ((threadIdx.x & 31) == 0) mbar_arrive(b); }

__device__ __forceinline__ void x_load(uint32_t sb, const uint8_t* img, int c) {
    const uint32_t bytes = c == 4 ? 8192 : 16384;
    mbar_expect(sb + E_BAR + (B_XF + c) * 8, bytes);
    bulk_g2s(sb + x_slot(c), img + c * 8192, bytes, sb + E_BAR + (B_XF + c) * 8);
}
__device__ __forceinline__ void x_ready(const uint32_t* f, uint32_t target) {
    asm volatile("{.reg .pred p; .reg .b32 v; W: ld.relaxed.gpu.global.u32 v, [%0]; sub.s32 v, v, %1; setp.lt.s32 p, v, 0; @p bra W;}" :: "l"(f), "r"(target) : "memory");
    fence_acq_gpu();
    fence_async_glb();
}

template <int N>
__device__ __forceinline__ uint32_t reduce_unit(const CUtensorMap* tm, int x, int y, uint32_t buf, uint32_t mb, uint32_t& ph, uint32_t tag, int lane, int& n, uint32_t prof_at) {
#pragma unroll 1
    while (true) {
        if (N == 16 && elect()) { mbar_expect(mb, N * 128); tma_2d(buf, tm, x, y, mb); }
        mbar_wait(mb, ph);
        ph ^= 1;
        float a[4];
        uint32_t v[N];
#pragma unroll
        for (int j = 0; j < N; j++) v[j] = lds32(buf + lane * 4 + j * 128);
#pragma unroll
        for (int j = 0; j < N; j++) {
            const int k = N == 16 ? 2 * (j & 1) : 0;
            a[k] = j < N / 8 ? bf_lo(v[j]) : a[k] + bf_lo(v[j]);
            a[k + 1] = j < N / 8 ? bf_hi(v[j]) : a[k + 1] + bf_hi(v[j]);
        }
        uint32_t bad = or3(xor_or(v[0], v[1], tag), xor_or(v[2], v[3], tag), xor_or(v[4], v[5], tag));
        if (N == 16) {
            bad = or3(bad, or3(xor_or(v[6], v[7], tag), xor_or(v[8], v[9], tag), xor_or(v[10], v[11], tag)), xor_or(v[12], v[13], tag));
            a[0] += a[2]; a[1] += a[3];
        }
#pragma unroll
        for (int o = 16; o >= (N == 16 ? 16 : 4); o >>= 1) { a[0] += __shfl_xor_sync(~0u, a[0], o); a[1] += __shfl_xor_sync(~0u, a[1], o); }
        if (!(__ballot_sync(~0u, or_bit0(bad, xor_or(v[N - 2], v[N - 1], tag))) & 0x11111111u)) return pack2(a[0], a[1]);
        if (N == 8 && elect()) { mbar_expect(mb, N * 128); tma_2d(buf, tm, x, y, mb); }
        RETRY(n, 1);
    }
    return 0;
}
__device__ __forceinline__ uint32_t ag_place(int tile, int layer, int t, int up, bool writes) {
    const int f = (blockIdx.x >> 4) * 16 + ((blockIdx.x >> 1) & 7) + up * 8;
    return opaque((m_pos(tile) * 128 + layer * 64 + f) * 16 + t * 4 + (((f >> 3) & 3) == t) + (writes ? 0 : 2));
}
__device__ __forceinline__ uint32_t mem0_word(const Params& P, int tile, uint32_t ag_dst) {
    const uint16_t* m = (const uint16_t*)P.mem0 + tile * 64 + ((ag_dst >> 4) & 63) + ((ag_dst >> 2) & 3) * (2 * DM);
    return (uint32_t)__ldg(m) | ((uint32_t)__ldg(m + DM) << 16);
}
__device__ __forceinline__ void ag_store(uint8_t* to, uint32_t w, uint32_t ag_dst, uint32_t atag) {
    asm volatile("{.reg .pred p; setp.eq.u32 p, %2, 0; @p st.relaxed.gpu.global.u32 [%0], %1;}" :: "l"(to), "r"(tagged(w, ag_dst & 1, atag)), "r"(ag_dst & 2) : "memory");
}

__device__ __forceinline__ void engine_a(const Params& P, uint32_t sb) {
    const uint32_t bars = sb + E_BAR;
    uint32_t w[KRQ][4];
    load_wregs<KRQ, 0>(w, sb);
    const int rank = blockIdx.x & 1;
    const uint32_t peer_off = mapa(sb, rank ^ 1) - sb;
    const int tid = opaque(threadIdx.x);
    const bool warp0 = __shfl_sync(~0u, tid, 0) == 0, lane0 = (tid & 31) == 0;
    const uint32_t row = opaque(sb + tile_row<false>(tid, rank));
    const int dq = opaque((tid >> 2) - 2 * (tid & 3));
#pragma unroll 1
    for (int i = 0; i < NSTEP; i++) {
        {
            const uint32_t xp = i & 1;
            float xq[32], xk[32], d[8];
            Walk wk[5];
#define W(c) x_wait(sb, c, xp);
#define Q(c) proj_x<KRQ, 1>(P, wk, xq, xk, w, E_WQ, c);
#define K(c) proj_x<KRQ, 2>(P, wk, xq, xk, w, E_WQ, c);
#define B(c) proj_x<KRQ, 3>(P, wk, xq, xk, w, E_WQ, c);
#define C wg_commit();
#define E C wg_wait<1>(); if (lane0) mbar_arrive(bars + B_E01 * 8); ES(0, 8); wg_fence();
#define M C wg_wait<1>(); if (lane0) mbar_arrive(bars + B_MF * 8); ES(0, 9); wg_fence();
#define T C wg_wait<1>(); if (lane0) { mbar_arrive_remote(bars + B_TF * 8 + peer_off); mbar_arrive(bars + B_TF * 8); } wg_fence();
            if (i > 0) nbar_sync(NB_WIA, 256);
            XSEQ
#undef W
#undef Q
#undef K
#undef B
#undef C
#undef E
#undef M
#undef T
            nbar_arrive(NB_XI, 256);
            const uint32_t t = keep(tid) & 3, own = row + t * (2 * TG), out = row - rank * 1024 + E_OUT + t * SG, ownq = own + E_QX + (t ? 0 : TG);
            ES(0, 10);
            mbar_wait(bars + B_TF * 8, xp);
            wg_wait<KEARLY>();
            park_x(xk, rank ? out : own + E_KX, rank ? own + E_KX : out);
            __syncwarp();
            wg_wait<0>();
            park_x(xq, rank ? out + 4 * SG : ownq, rank ? ownq : out + 4 * SG);
            fence_async_smem();
            __syncwarp();
            if (lane0) mbar_arrive(bars + B_RF * 8);
            ES(0, 11);
            mbar_wait(bars + B_ML * 8, xp);
            ES(0, 5);
            proj_mem<KRQ, true>(P.dMq, d, w, E_WQ);
            mbar_wait(bars + B_M * 8, xp);
            const bool redo = __shfl_sync(~0u, lds32(sb + E_REDO), 0) == i + 1;
            wg_wait<0>();
            if (redo) {
                proj_mem<KRQ, false>(P.dMq2, d, w, E_WQ);
                wg_wait<0>();
            }
            put_mem<false>(d, row + E_QM + t * 4, rank, peer_off, bars + B_QK * 8);
            __syncwarp();
            if (lane0) { mbar_expect(bars + B_QK * 8, (2048 + 8192) / 4); mbar_arrive(bars + B_PD * 8); }
        }
        const uint32_t par = i & 1;
        ES(0, 1);
        uint32_t pa[12];
        float s0, s1;
        uint32_t a, o_dst;
        {
            float s[20];
            constexpr float MASKED = -1e9f / SM_SCALE;
            const int dl = keep(warp0 ? 64 : dq);
#pragma unroll
            for (int j = 0; j < 20; j++) s[j] = j >= 16 || (j > 4 && (j & 2)) || (j >> 2) * 8 + (j & 1) <= (j & 2 ? dq : dl) ? 0.f : MASKED;
#pragma unroll
            for (int j = 3; j < 12; j++)
                if (j == 3 || j == 5 || j == 7 || j >= 10) asm volatile("lop3.b32 %0, %1, %2, %3, 0x28;" : "=r"(pa[j]) : "r"(dq), "r"(j), "r"(P.zero));
            {
                const int t = keep(tid);
                a = sb + E_OM + rank * 2048 + (t >> 2) * 128 + (((t ^ (t >> 2)) & 3) << 4) + (t & 16) * 4;
                o_dst = ((i & (RING - 1)) * 64 + (blockIdx.x & ~1)) * 8192 + rank * 2048 + (t >> 2) * 64 + (((t ^ (t >> 3)) & 3) << 4);
                pin(P, a | o_dst);
            }
            uint64_t da = P.dQ, db = P.dK;
            mbar_wait_cl(bars + B_QK * 8, par);
            CFENCE;
            ES(0, 2);
            wg_fence();
#pragma unroll
            for (int ks = 0; ks < 8; ks++) { wg_ss40<1>(s, da, db, 1); if (ks < 7) { dmove(da, 16); dmove(db, 16); } }
            wg_commit();
            nbar_arrive(NB_SI, 256);
            wg_wait<0>();
            ES(0, 3);
            float m0 = fmaxf(fmaxf(fmaxf(s[0], s[1]), fmaxf(s[4], s[5])), fmaxf(fmaxf(fmaxf(s[8], s[9]), fmaxf(s[12], s[13])), fmaxf(s[16], s[17])));
            float m1 = fmaxf(fmaxf(s[2], s[3]), fmaxf(s[18], s[19]));
#pragma unroll
            for (int x = 1; x <= 2; x++) { m0 = fmaxf(m0, __shfl_xor_sync(~0u, m0, x)); m1 = fmaxf(m1, __shfl_xor_sync(~0u, m1, x)); }
            m0 *= SM_SCALE * LOG2E;
            m1 *= SM_SCALE * LOG2E;
#pragma unroll
            for (int j = 0; j < 20; j++) if (!(j & 2) || j < 4 || j >= 16) s[j] = ex2(fmaf(s[j], SM_SCALE * LOG2E, j & 2 ? -m1 : -m0));
#pragma unroll
            for (int m = 0; m < 5; m++) pa[2 * m] = pack2(s[4 * m], s[4 * m + 1]);
            pa[1] = pack2(s[2], s[3]);
            pa[9] = pack2(s[18], s[19]);
            s0 = ((s[0] + s[1]) + (s[4] + s[5])) + ((s[8] + s[9]) + (s[12] + s[13])) + (s[16] + s[17]);
            s1 = (s[2] + s[3]) + (s[18] + s[19]);
        }
        {
            float o[64];
            ES(0, 4);
            mbar_wait_cl(bars + B_V * 8, par);
            CFENCE;
            wg_fence();
#pragma unroll
            for (int u = 0; u < 2; u++) {
                wg_rs64<0>(o + 32 * u, &pa[0], mkdesc(E_VX + u * 1024, 2 * TG, 128, 0), 0);
                wg_rs64<0>(o + 32 * u, &pa[4], mkdesc(E_VX + u * 1024 + 4 * TG, 2 * TG, 128, 0), 1);
                wg_rs64<0>(o + 32 * u, &pa[8], mkdesc(E_VM + u * 1024, 0, 128, 0), 1);
                wg_commit();
            }
            nbar_arrive(NB_PVI, 256);
#define OCHUNK(jj) make_uint4(pack2(o[16 * (jj)], o[16 * (jj) + 1]), pack2(o[16 * (jj) + 4], o[16 * (jj) + 5]), pack2(o[16 * (jj) + 8], o[16 * (jj) + 9]), pack2(o[16 * (jj) + 12], o[16 * (jj) + 13]))
            const uint32_t one = lds32(sb + E_ONE);
            s0 += __shfl_xor_sync(~0u, s0, one); s1 += __shfl_xor_sync(~0u, s1, one);
            pin(P, __float_as_uint(s0) | __float_as_uint(s1));
            const float r0 = __shfl_xor_sync(~0u, s0, 2), r1 = __shfl_xor_sync(~0u, s1, 2);
            wg_wait<1>();
            ES(0, 6);
            if (warp0) { st_async128(a + peer_off, OCHUNK(0), bars + B_OM * 8 + peer_off); st_async128((a ^ 64) + peer_off, OCHUNK(1), bars + B_OM * 8 + peer_off); }
            float inv = rcp(s0 + r0);
            if (tid < 32 && !(tid & 3)) {
                st_async32(sb + E_INV + rank * 32 + tid + peer_off, __float_as_uint(inv), bars + B_OM * 8 + peer_off);
                sts32(sb + E_INV + rank * 32 + tid, __float_as_uint(inv));
            }
            __syncwarp();
            wg_wait<0>();
            if (warp0) {
                const uint4 m2 = OCHUNK(2), m3 = OCHUNK(3);
                st_async128(a + 1024 + peer_off, m2, bars + B_OM * 8 + peer_off);
                st_async128((a ^ 64) + 1024 + peer_off, m3, bars + B_OM * 8 + peer_off);
                sts128(a + 1024, m2); sts128((a ^ 64) + 1024, m3);
                sts128(a, OCHUNK(0)); sts128(a ^ 64, OCHUNK(1));
                __syncwarp();
                inv = rcp(s1 + r1);
            }
            if (lane0) mbar_expect(bars + B_OM * 8, (2048 + 32) / 4);
            ES(0, 7);
#pragma unroll
            for (int j = 0; j < 32; j++) o[(j >> 1) * 4 + (j & 1)] = (warp0 ? o[(j >> 1) * 4 + 2 + (j & 1)] : o[(j >> 1) * 4 + (j & 1)]) * inv;
#pragma unroll
            for (int jj = 0; jj < 4; jj++) stg128(g_o + o_dst + jj * 4096, OCHUNK(jj));
#undef OCHUNK
            nbar_arrive(NB_WIB, NTHREADS);
        }
    }
    mbar_wait(bars + B_OM * 8, (NSTEP - 1) & 1);
}

__device__ __forceinline__ void engine_b(const Params& P, uint32_t sb) {
    const uint32_t bars = sb + E_BAR;
    uint32_t w[KRV][4];
    load_wregs<KRV, 1>(w, sb);
    const int rank = blockIdx.x & 1;
    const uint32_t peer_off = mapa(sb, rank ^ 1) - sb;
    const int tid = threadIdx.x & 127, warp = __shfl_sync(~0u, tid >> 5, 0);
    const bool lane0 = opaque(tid & 31) == 0;
    const uint32_t ax = opaque(sb + E_VX + tile_row<true>(tid, rank) + (tid & 3) * (2 * TG));
    const uint32_t am = opaque(sb + E_VM + tile_row<true>(tid, rank) + (tid & 3) * 4);
    uint32_t j0, j1 = ag_place(8, rank, tid & 3, warp & 1, (tid & 31) < 4), ph = 0;
    if (warp == 0) {
        const int kg = ((blockIdx.x & ~1) + tid) / 13;
        j0 = opaque((blockIdx.x & ~1) * 8192 + rank * 2048 + (tid >> 4) * 4096 + (tid & 15) * 128);
        j1 = opaque(tid == 0 || (tid == 1 && kg * 13 == (blockIdx.x | 1)) ? (F_O + kg) * sizeof(g_flag[0]) : 0);
    } else {
        j0 = mem0_word(P, 8, j1);
    }
    const uint32_t e1 = __shfl_sync(~0u, lds32(sb + E_EPOCH), 0) + 1;
    const uint8_t* img = g_xe;
    if (warp == 0) {
        x_ready(g_flag[F_XE][0], e1 * 96);
        TV(128, 126, 8, gtl());
        fence_async_smem();
        if (elect()) { x_load(sb, img, 0); x_load(sb, img, 2); }
    }
#pragma unroll 1
    for (int i = 0; i < NSTEP; i++) {
        {
            const uint32_t xp = i & 1;
            float xv[32];
            Walk wk[2];
#define XB(c) x_wait(sb, c, xp); proj_x<KRV, 1>(P, wk, xv, xv, w, E_WV, c); wg_commit()
#pragma unroll
            for (int c = 0; c < GB1; c++) { XB(c); }
            if (i > 0) nbar_sync(NB_PVI, 256);
#pragma unroll
            for (int c = GB1; c < GB1 + GB2; c++) { XB(c); }
            ES(128, 14);
            if (warp == 0) {
                if (i > 0) mbar_wait(bars + B_OM * 8, xp ^ 1);
                if (elect()) { x_load(sb, img, 4); x_load(sb, img, 5); }
            }
            wg_wait<0>();
            if (lane0) { mbar_arrive(bars + B_E01 * 8); mbar_arrive(bars + B_MF * 8); }
            if (i > 0) nbar_sync(NB_WIB, NTHREADS);
#pragma unroll
            for (int c = 4; c < 4 + GB3; c++) { XB(c); }
            if (warp == 0) {
                if (i > 0) {
                    const uint8_t* o = g_o + ((i - 1) & (RING - 1)) * (64 * 8192) + j0;
                    const uint32_t v = ld_rlx((const uint32_t*)o) | ld_rlx((const uint32_t*)(o + 8192));
                    if (j1) flag_signal_after(P, (uint32_t*)((uint8_t*)g_flag[0][i - 1] + j1), v);
                    ES(0, 17);
                }
            } else if (warp == 1) {
                mbar_wait(bars + B_E01 * 8, xp);
                if (X7_DELAY) spin_cycles(X7_DELAY);
                if (elect()) x_load(sb, img, 7);
            } else {
                const uint32_t ra = (e1 - 1) * NSTEP + i, rr = ra - e1;
                uint32_t w9 = j0;
                if (i > 0) {
                    int n = 0;
                    const int l1 = fresh_tid() & 31;
                    ES(192, 12);
                    w9 = reduce_unit<8>(&P.tmR9, 1792 + rank * 256 + warp * 128 + (blockIdx.x >> 1) * 4, (rr & 1) * 64, sb + E_RS + 6144 + warp * 1024, bars + (B_R9 - 2 + warp) * 8, ph,
                                           ((rr >> 1) & 1) ^ 1, l1, n, sb + E_BAR + 128 + (xp ^ 1) * 128 + 29 * 4);
                    EV(192, 25, n);
                }
                if (rank && i == LAG) w9 = j0;
                ag_store(g_ag + ((ra & 1) * 18432 + (keep(j1) & ~3u)), w9, j1, ((ra >> 1) & 1) ^ 1);
                ES(192, 0);
            }
            ES(128, 28);
#pragma unroll
            for (int c = 4 + GB3; c < 7; c++) { XB(c); }
            wg_wait<0>();
            if (lane0) { mbar_arrive_remote(bars + B_TF * 8 + peer_off); mbar_arrive(bars + B_TF * 8); }
            nbar_sync(NB_XI, 256);
            XB(7); XB(8);
#undef XB
            wg_wait<0>();
            if (lane0) mbar_arrive(bars + B_RF * 8);
            ES(128, 15);
            img += XIMG;
            if (warp == 1 && i < NSTEP - 1) x_ready(g_flag[F_XE][i + 1], e1 * 96);
            mbar_wait(bars + B_TF * 8, xp);
            mbar_wait(bars + (B_EARLY ? B_ML : B_M) * 8, xp);
            if (warp < 2) {
                mbar_wait(bars + B_RF * 8, xp);
                if (elect()) {
                    if (warp == 0) {
#pragma unroll 1
                        for (int j = 0; j < 4; j++) {
                            const uint32_t o = sb + j * (2 * TG) + rank * 1024 + peer_off;
                            bulk_s2peer(o + E_KX, sb + E_OUT + j * SG, 1024, bars + B_QK * 8 + peer_off);
                            bulk_s2peer(o + E_QX + (j ? 0 : TG), sb + E_OUT + (j + 4) * SG, 1024, bars + B_QK * 8 + peer_off);
                        }
                    } else if (i < NSTEP - 1) {
                        x_load(sb, img, 0);
                    }
                }
            }
            put_xv(xv, ax, rank, peer_off, bars + B_V * 8);
        }
        ES(128, 16);
        float d[8];
        nbar_sync(NB_QKI, NTHREADS);
        proj_mem<KRV, false>(P.dMv, d, w, E_WV);
        wg_wait<0>();
        put_mem<true>(d, am, rank, peer_off, bars + B_V * 8);
        __syncwarp();
        if (lane0) { mbar_expect(bars + B_V * 8, (1024 + 4096) / 4); mbar_arrive(bars + B_PD * 8); }
        ES(128, 18);
        nbar_sync(NB_SI, 256);
    }
    nbar_sync(NB_PVI, 256);
    nbar_sync(NB_WIB, NTHREADS);
    if (warp == 0 && j1) flag_signal((uint32_t*)((uint8_t*)g_flag[0][NSTEP - 1] + j1));
}

__device__ __forceinline__ void engine_c(const Params& P, uint32_t sb) {
    const uint32_t bars = sb + E_BAR;
    const int e = blockIdx.x, rank = e & 1;
    const int tid = opaque(threadIdx.x & 127), lane = tid & 31, warp = __shfl_sync(~0u, tid >> 5, 0);
#pragma unroll 1
    for (int round = 0; round < 2; round++) {
        if (tid == 0) {
            fence_async_smem();
            mbar_expect(bars + B_WL * 8, (round ? KRQ + KRV - 2 * E_ST1 : 2 * E_ST1) * 2048);
            mbar_expect(bars + (round ? B_WO : B_WS) * 8, round ? 36 * 2048 : E_RING - 36 * 2048);
        }
        nbar_sync(NB_C, 128);
        const int j = round * E_ST1 + lane, k = tid - 64 - (warp - 2) * 14;
        if (warp == 0) {
            if (lane < E_ST1 && j < KRQ) tma_w(sb + e_stage(lane), &P.tmWq, Res<KRQ>::step(j), e, bars + B_WL * 8);
            if (!round && lane < 36 - KRQ) tma_w(sb + E_WQ + lane * 2048, &P.tmWq, S0Q + lane, e, bars + B_WS * 8);
        } else if (warp == 1) {
            if (lane < E_ST1 && j < KRV) tma_w(sb + e_stage(E_ST1 + lane), &P.tmWv, Res<KRV>::step(j), e, bars + B_WL * 8);
            if (!round && lane < 36 - KRV) tma_w(sb + E_WV + lane * 2048, &P.tmWv, S0V + lane, e, bars + B_WS * 8);
        } else {
            spin_cycles(1200);
            if (lane < 18) {
                if (!round) tma_w(sb + E_WK + (m_pos(k >> 2) * 4 + (k & 3)) * 2048, &P.tmWk, k, e, bars + B_WS * 8);
                else tma_w(sb + E_WO + k * 2048, &P.tmWo, k < 32 ? (e >> 1) * 8 + (k & 7) : e * 4 + k - 32, k < 32 ? rank * 4 + (k >> 3) : 8, bars + B_WO * 8);
            }
        }
        if (!round) nbar_sync(NB_ALL, NTHREADS);
    }
    cluster_wait();
    const uint32_t peer_off = mapa(sb, rank ^ 1) - sb;
    const uint32_t epoch = __shfl_sync(~0u, lds32(sb + E_EPOCH), 0);
    const uint32_t ag_dst = ag_place(rank * 4 + warp, (lane >> 1) & 1, (lane >> 2) & 3, lane & 1, lane < 16), w_init = mem0_word(P, rank * 4 + warp, ag_dst);
    const uint32_t k_dst = opaque(sb + E_KM + tile_row<false>(tid, rank) + (tid & 3) * 4);
    const bool lane0 = lane == 0;
    uint32_t rr = epoch * (NSTEP - 1) - 1, ra = epoch * NSTEP, ph = 0;
    mbar_wait(bars + B_WS * 8, 0);
#pragma unroll 1
    for (int i = -1; i < NSTEP; i++, rr++, ra++) {
        const uint32_t par = i & 1;
        uint32_t w0 = w_init;
        const uint32_t atag = ((ra >> 1) & 1) ^ 1;
        uint8_t* const ag_to = g_ag + ((ra & 1) * 18432 + (ag_dst & ~3u));
        if (i >= 0) {
            const uint32_t tag = ((rr >> 1) & 1) ^ 1;
            uint32_t mine, latest;
            {
                float d[8];
                uint64_t da = P.dWk, db = P.dMk;
#pragma unroll
                for (int j = 0; j < 8; j++) d[j] = 0.f;
#pragma unroll 1
                for (int p = P.zero; p < KLOOP; p++) {
                    wg_fence();
#pragma unroll
                    for (int j = 0; j < 36 / KLOOP; j++) { wg_ss16<1>(d, da, db, 1); dmove(da, 128); dmove(db, (j & 3) < 3 ? 16 : 80); }
                    wg_commit();
                }
                nbar_arrive(NB_QKI, NTHREADS);
                wg_wait<0>();
                put_mem<false>(d, k_dst, rank, peer_off, bars + B_QK * 8);
                __syncwarp();
                if (lane0) { mbar_arrive(bars + B_QK * 8); mbar_arrive(bars + B_PD * 8); }
                ES(256, 13);
                if (i == NSTEP - 1) break;
                mbar_wait(bars + B_QK * 8, par);
                unsigned long long now;
                asm volatile("mov.u64 %0, %%globaltimer;" : "=l"(now));
                const uint32_t t0 = clock32();
                if (tid == 0) asm volatile("red.relaxed.gpu.global.max.u64 [%0], %1;" :: "l"(&g_latest), "l"(now) : "memory");
                mine = (uint32_t)now;
                if (warp == 3) {
                    mbar_wait(bars + B_PD * 8, par);
                    if (elect()) x_load(sb, g_xe + (i + 1) * XIMG, 2);
                    EFLUSH(i - 1);
                }
                mbar_wait(bars + B_WO * 8, 0);
                while ((int)(clock32() - t0) < LATE_WAIT) {}
                latest = ld_rlx((const uint32_t*)&g_latest);
            }
            {
                float y[4][8];
                uint64_t db = P.dOm + rank * 64, da = P.dWo + 32 * 128;
                const uint32_t inv_at = opaque(sb + E_INV + (tid & 3) * 8);
                uint8_t* const dst = g_rs + (size_t)opaque(((rr & 1) * NENG + e) * 10240 + tid * 16);
#define W_TILE(Y, F) { _Pragma("unroll") for (int ks = 0; ks < 8; ks++) { wg_ss16<0>(y[Y], da, db, ks > 0 ? 1 : F); dmove(da, 128); dmove(db, ks == 7 ? -70 : ks == 3 ? 58 : 2); } wg_commit(); }
#define WORD(Y, k) pack2(y[Y][2 * (k)] * __uint_as_float((k) < 2 ? i0.x : i1.x), y[Y][2 * (k) + 1] * __uint_as_float((k) < 2 ? i0.y : i1.y))
#define W_ST(Y, T) { st_rlx128(dst + (T) * 2048, make_uint4((WORD(Y, 0) & ~1u) | tag, WORD(Y, 1), WORD(Y, 2), WORD(Y, 3))); __syncwarp(); }
                mbar_wait_cl(bars + B_OM * 8, par);
                CFENCE;
                ES(256, 19);
                const uint2 i0 = lds64(inv_at), i1 = lds64(inv_at + 32);
                wg_fence();
#pragma unroll
                for (int ks = 0; ks < 4; ks++) { wg_ss16<0>(y[0], da, db, ks > 0); dmove(da, ks < 3 ? 128 : -35 * 128); if (ks < 3) dmove(db, 2); }
                wg_commit();
                db = P.dOm;
                W_TILE(1, 0);
                W_TILE(2, 0);
                wg_wait<2>();
#pragma unroll
                for (int k = 0; k < 4; k++) st_rlx32(dst + 8192 + k * 512 - tid * 12, tagged(WORD(0, k), (tid & 3) == 0, tag));
                __syncwarp();
                wg_fence();
                W_TILE(3, 0);
                wg_wait<2>(); W_ST(1, 0);
                wg_fence();
                W_TILE(0, -1);
                wg_wait<2>(); W_ST(2, 1);
                wg_wait<1>(); W_ST(3, 2);
                nbar_arrive(NB_WIB, NTHREADS);
                nbar_arrive(NB_WIA, 256);
                wg_wait<0>(); W_ST(0, 3);
#undef W_TILE
#undef W_ST
#undef WORD
            }
            const uint32_t t0 = clock32();
            ES(352, 20);
            const int w1 = keep(warp), x0 = rank * 2560 + w1 * 512 + (e >> 1) * 16;
            const int lag = min(max((int)(latest - mine), 0), 1000) * LATE_MUL / 4, dly = RS_DELAY - (3 - w1) * RS_SKEW + lag;
            int n = 0;
            EV(0, 30, dly);
            if (w1 >= 2) {
                while ((int)(clock32() - t0) < RS_DELAY0 + lag) {}
                if (elect()) {
                    mbar_expect(bars + (B_R9 - 2 + w1) * 8, 1024);
                    tma_2d(sb + E_RS + 6144 + w1 * 1024, &P.tmR9, 1792 + rank * 256 + w1 * 128 + (e >> 1) * 4, (rr & 1) * 64, bars + (B_R9 - 2 + w1) * 8);
                }
            }
            while ((int)(clock32() - t0) < dly) {}
            w0 = reduce_unit<16>(&P.tmRs, x0, (rr & 1) * 32, sb + E_RS + w1 * 2048, bars + (B_RS + w1) * 8, ph, tag, keep(tid) & 31, n, sb + E_BAR + 128 + par * 128 + 21 * 4);
            EV(352, 26, n);
            if (i == LAG - 1 && (ag_dst & 1024)) w0 = w_init;
        }
        ag_store(ag_to, w0, ag_dst, atag);
        ES(352, 22);
        if (lane0) { mbar_arrive_remote(bars + B_TF * 8 + peer_off); mbar_arrive(bars + B_TF * 8); }
        const int w1 = keep(warp), l1 = keep(tid) & 31;
        const uint32_t dst = sb + E_MEM + w1 * 4608, mb = bars + (B_RS + w1) * 8, chk = dst + l1 * 16 + (l1 >> 3) * 4;
        const uint8_t* src = g_ag + ((ra & 1) * 18432 + w1 * 4608);
        const bool one = elect();
        mbar_wait(bars + B_MF * 8, par ^ 1);
        const uint32_t t1 = clock_after(nbar_any(NB_C, 128, 0));
        int n = 0;
        if (w1 == 0) {
            while ((int)(clock32() - t1) < AG_DELAY) {}
            if (one) { mbar_expect(bars + B_ML * 8, 18432); bulk_g2s(dst, src, 18432, bars + B_ML * 8); }
        }
        mbar_wait(bars + B_ML * 8, par ^ 1);
#pragma unroll 1
        while (true) {
            uint32_t v[9];
#pragma unroll
            for (int j = 0; j < 9; j++) v[j] = lds32(chk + j * 512);
            if (!__any_sync(~0u, or_bit0(xor_or(v[0], v[1], atag) | xor_or(v[2], v[3], atag) | xor_or(v[4], v[5], atag), xor_or(v[6], v[7], atag) | (v[8] ^ atag)))) break;
            if (one) { sts32(sb + E_REDO, i + 2); mbar_expect(mb, 4608); bulk_g2s(dst, src, 4608, mb); }
            RETRY(n, 2);
            mbar_wait(mb, ph);
            ph ^= 1;
        }
        ES(352, 23); EV(352, 27, n);
        if (one) {
            mbar_arrive(bars + B_M * 8);
            if (n) {
                unsigned long long now;
                asm volatile("mov.u64 %0, %%globaltimer;" : "=l"(now));
                asm volatile("red.relaxed.gpu.global.max.u64 [%0], %1;" :: "l"(&g_latest), "l"(now + LATE_NS) : "memory");
            }
        }
        nbar_sync(NB_C, 128);
    }
    nbar_arrive(NB_WIB, NTHREADS);
    if (e == 0 && tid == 0) g_epoch = lds32(sb + E_EPOCH) + 1;
}

enum { ST_WO = 0, ST_F2 = 1, ST_F1 = 2 };
template <int ST> struct Stage;
template <> struct Stage<ST_WO> { static constexpr int NKS = 52, NR0 = 37, NR1 = 45, NT1 = 1, NSLOT = 8, TB = 0; };
template <> struct Stage<ST_F2> { static constexpr int NKS = 58, NR0 = 37, NR1 = 45, NT1 = 1, NSLOT = 5, TB = 1; };
template <> struct Stage<ST_F1> { static constexpr int NKS = 36, NR0 = F1_NR, NR1 = F1_NR, NT1 = 2, NSLOT = F1_SLOTS, TB = 0; };
template <int ST> struct StageMap : Stage<ST> {
    using S = Stage<ST>;
    static constexpr int NCH = (S::NKS + 3) / 4;
    static constexpr int W0A = 0, W0B = W0A + (S::NKS - S::NR0) * 2048, W1A = W0B + S::NKS * 2048, W1B = W1A + (S::NKS - S::NR1) * 2048;
    static constexpr int RNG = W1B + (S::NT1 - 1) * S::NKS * 2048;
    static constexpr int ROWS = RNG + S::NSLOT * 8192;
    static_assert(ROWS + (ST == ST_F1 ? 3 * 6912 : 0) <= SM_BAR && (S::NR0 + S::NR1) * 2048 <= SM_BAR, "stage smem");
};
__host__ __device__ constexpr int rs_idx(int ks, int nr, int nks) { return ks * nr / nks; }
__host__ __device__ constexpr bool is_rs(int ks, int nr, int nks) { return rs_idx(ks + 1, nr, nks) > rs_idx(ks, nr, nks); }

template <int ST, int SHAPE>
__device__ __forceinline__ void stage_consumer(const Params& P, uint32_t sb, int idx, const int WG) {
    using M = StageMap<ST>;
    constexpr int NR = SHAPE ? M::NR1 : M::NR0, NT = SHAPE ? M::NT1 : 2, NKS = M::NKS;
    const uint32_t bars = sb + SM_BAR;
    uint32_t w[NR][4];
    {
        const uint32_t base = frag_addr(sb + WG * (M::NR0 * 2048));
        mbar_wait(bars + B_WL * 8, 0);
#pragma unroll
        for (int r = 0; r < NR; r++) ldsm4t(w[r], base + r * 2048);
        TV(0, 126, 4, gtl());
        nbar_sync(NB_ALL, 288);
        mbar_wait(bars + B_WS * 8, 0);
        TV(0, 126, 7, gtl());
    }
    const bool shortk = ST != ST_F1 && idx >= 12;
    uint32_t s = 0, ph = 0, use = __shfl_sync(~0u, lds32(sb + SM_EPOCH), 0) * NSTEP;
#pragma unroll 1
    for (int j = 0; j < NSTEP; j++, use++) {
        float d[NT][32];
        uint64_t da0 = P.d128 + WG * (M::W1A / 16), da1 = da0 + (NKS - NR) * 128;
        uint32_t prev = 0;
#pragma unroll
        for (int c = 0; c < M::NCH; c++) {
            if (c < M::NCH - 1 || !shortk) {
                mbar_wait(bars + (B_FULL + s) * 8, ph);
                if (c == 0) TS(WG * 128, j, WG * 4);
                uint64_t b = (ST == ST_WO ? P.d64 : P.d128) + (M::RNG / 16 + s * 512);
                wg_fence();
#pragma unroll
                for (int kk = 0; kk < 4; kk++) {
                    const int ks = c * 4 + kk;
                    if (ks < NKS) {
                        if (is_rs(ks, NR, NKS)) wg_rs64<M::TB>(d[0], w[rs_idx(ks, NR, NKS)], b, ks > 0);
                        else { wg_ss64<M::TB>(d[0], da0, b, ks > 0); dmove(da0, 128); }
                        if (NT > 1) { wg_ss64<M::TB>(d[NT - 1], da1, b, ks > 0); dmove(da1, 128); }
                        if (kk < 3) dmove(b, ST == ST_WO ? (kk == 1 ? 254 : 2) : M::TB ? 128 : 2);
                    }
                }
                wg_commit();
                if (c > 0) {
                    wg_wait<1>();
                    if ((fresh_tid() & 31) == 0) mbar_arrive(prev);
                }
                prev = bars + (B_EMPTY + s) * 8;
                if (++s == M::NSLOT) { s = 0; ph ^= 1; }
            }
        }
        const int tid = fresh_tid(), g = (tid >> 2) & 7, t = tid & 3, warp = (tid >> 5) & 3;
        wg_wait<0>();
        if ((tid & 31) == 0) mbar_arrive(prev);
        TS(WG * 128, j, WG * 4 + 1);
        if (ST == ST_F1) {
            uint8_t* dst = g_h + ((j & (RING - 1)) * FF + idx * 128 + WG * 64 + warp * 16 + g) * 128;
#pragma unroll
            for (int h = 0; h < 2; h++) {
#pragma unroll
                for (int c = 0; c < 2; c++) {
                    uint32_t pk[4];
#pragma unroll
                    for (int m = 0; m < 4; m++) {
                        const int o = 16 * c + 4 * m + 2 * h;
                        const float g0 = d[0][o], g1 = d[0][o + 1];
                        const float e0 = 1.f + ex2(fminf(-LOG2E * g0, 60.f)), e1 = 1.f + ex2(fminf(-LOG2E * g1, 60.f));
                        const float r = rcp(e0 * e1);
                        pk[m] = pack2(g0 * d[NT - 1][o] * (e1 * r), g1 * d[NT - 1][o + 1] * (e0 * r));
                    }
                    stg128(dst + h * 1024 + (((c * 4 + t) ^ g) << 4), make_uint4(pk[0], pk[1], pk[2], pk[3]));
                }
            }
            TS(WG * 128, j, WG * 4 + 2);
            __syncwarp();
            const uint32_t z = nbar_any(NB_WG0 + WG, 128, ld_rlx((const uint32_t*)(dst + (t & 1) * 1024)) & P.zero);
            const int f0 = idx * 128 + WG * 64, kg = (f0 + (tid & 1) * 63) / 928;
            if ((tid & 127) == 0 || ((tid & 127) == 1 && kg * 928 > f0)) red_add_u32(g_flag[F_H + kg][j], z + 1);
            TS(WG * 128, j, WG * 4 + 3);
        } else {
            uint8_t* dst = g_part[ST & 1] + (((use & (RING - 1)) * 64 + g) * 5 + idx / 3) * 1152 + ((idx % 3) * 3 + WG) * 128 + warp * 32 + t * 8;
            const uint32_t tag = ((use / RING) & 1) ^ 1, tm = ~t & 1;
#pragma unroll
            for (int m = 0; m < 8; m++) {
#pragma unroll
                for (int T = 0; T < NT; T++)
                    st_rlx64(dst + T * 256 + m * (8 * 5760), tagged(movm(pack2(d[T][4 * m], d[T][4 * m + 1])), tm, tag), movm(pack2(d[T][4 * m + 2], d[T][4 * m + 3])));
            }
            warp_arrive(bars + B_PUB * 8);
            TS(WG * 128, j, WG * 4 + 2);
        }
    }
}

template <int ST>
__device__ __forceinline__ void stage_producer(const Params& P, uint32_t sb, int idx) {
    using M = StageMap<ST>;
    const uint32_t bars = sb + SM_BAR;
    const int lane = threadIdx.x & 31;
    const int kg = ST == ST_F1 ? 0 : idx / 3;
    {
        const CUtensorMap* tm0 = ST == ST_WO ? &P.tmWo : ST == ST_F2 ? &P.tmW2 : &P.tmW1;
        const CUtensorMap* tm1 = ST == ST_F1 ? &P.tmW3 : tm0;
        const int k0 = kg * M::NKS, g0 = ST == ST_F1 ? idx * 2 : (idx % 3) * 3;
        constexpr int PACE = ST == ST_WO ? WO_PACE : ST == ST_F1 ? F1_PACE : F2_PACE;
        spin_cycles(ST == ST_WO ? WO_DELAY : G_DELAY);
        if (lane == 0) mbar_expect(bars + B_WL * 8, (M::NR0 + M::NR1) * 2048);
        __syncwarp();
#pragma unroll 1
        for (int ks = lane; ks < M::NKS + lane; ks += 4) {
            if (lane < 4 && ks < M::NKS) {
                if (is_rs(ks, M::NR0, M::NKS)) tma_w(sb + rs_idx(ks, M::NR0, M::NKS) * 2048, tm0, k0 + ks, g0, bars + B_WL * 8);
                if (is_rs(ks, M::NR1, M::NKS)) tma_w(sb + (M::NR0 + rs_idx(ks, M::NR1, M::NKS)) * 2048, tm0, k0 + ks, g0 + 1, bars + B_WL * 8);
            }
            __syncwarp();
            if (PACE) spin_cycles(PACE);
        }
        nbar_sync(NB_ALL, 288);
        if (lane == 0) { fence_async_smem(); mbar_expect(bars + B_WS * 8, M::RNG); }
        __syncwarp();
#pragma unroll 1
        for (int ks = lane; ks < M::NKS + lane; ks += 4) {
            if (lane < 4 && ks < M::NKS) {
                if (!is_rs(ks, M::NR0, M::NKS)) tma_w(sb + M::W0A + (ks - rs_idx(ks, M::NR0, M::NKS)) * 2048, tm0, k0 + ks, g0, bars + B_WS * 8);
                if (!is_rs(ks, M::NR1, M::NKS)) tma_w(sb + M::W1A + (ks - rs_idx(ks, M::NR1, M::NKS)) * 2048, tm0, k0 + ks, g0 + 1, bars + B_WS * 8);
                tma_w(sb + M::W0B + ks * 2048, tm1, k0 + ks, ST == ST_F1 ? g0 : g0 + 2, bars + B_WS * 8);
                if (ST == ST_F1) tma_w(sb + M::W1B + ks * 2048, tm1, k0 + ks, g0 + 1, bars + B_WS * 8);
            }
            __syncwarp();
            if (PACE) spin_cycles(PACE);
        }
    }
    if (lane != 0) return;
    const uint32_t e1 = lds32(sb + SM_EPOCH) + 1;
    const uint32_t target = e1 * (ST == ST_F1 ? 32 : ST == ST_WO ? (kg < 4 ? 14 : 12) : (kg < 4 ? 15 : 14));
    const int nch = M::NCH - (kg == 4);
    uint32_t s = 0, ph = 1;
#pragma unroll 1
    for (int j = 0; j < NSTEP; j++) {
        const int slot = j & (RING - 1);
        const uint8_t* src = ST == ST_F1 ? g_xf + slot * XIMG : ST == ST_WO ? g_o + (slot * 64 + kg * 13) * 8192 : g_h + (slot * FF + kg * 928) * 128;
        flag_poll(g_flag[ST == ST_F1 ? F_XF : (ST == ST_WO ? F_O : F_H) + kg][j], ST == ST_F1 && j > LAG && j <= NSEG ? 2 * target : target);
        fence_acq_gpu();
        fence_async_glb();
        TS(256, j, 8);
#pragma unroll 1
        for (int c = 0; c < nch; c++) {
            const uint32_t bytes = (ST == ST_F2 && c == M::NCH - 1) ? 4096 : 8192;
            mbar_wait(bars + (B_EMPTY + s) * 8, ph);
            mbar_expect(bars + (B_FULL + s) * 8, bytes);
            bulk_g2s(sb + M::RNG + s * 8192, src + c * 8192, bytes, bars + (B_FULL + s) * 8);
            if (++s == M::NSLOT) { s = 0; ph ^= 1; }
        }
    }
}

template <int ST>
__device__ __forceinline__ void stage_split(const Params& P, uint32_t sb, int wg, int idx) {
    if (wg == 0) { reg_inc<240>(); stage_consumer<ST, 0>(P, sb, idx, 0); }
    else if (wg == 1) { reg_inc<240>(); stage_consumer<ST, 1>(P, sb, idx, 1); }
    else {
        reg_dec<24>();
        const int tid = fresh_tid();
        if (tid < 288) stage_producer<ST>(P, sb, idx);
        else if (tid == 288) {
#pragma unroll 1
            for (int j = 0; j < NSTEP; j++) {
                mbar_wait(sb + SM_BAR + B_PUB * 8, j & 1);
                red_add_u32(g_flag[F_PW + ST][j], 1);
                TS(288, j, 9);
            }
        }
    }
}

#define NOG
__global__ void __cluster_dims__(2, 1, 1) __launch_bounds__(NTHREADS, 1) fused_kernel(const __grid_constant__ Params P) {
    extern __shared__ __align__(1024) uint8_t smem_raw[];
    const uint32_t sb = smem_u32(smem_raw);
    const int tid = threadIdx.x;
    const int wg = __shfl_sync(~0u, tid >> 7, 0);
    const int bid = blockIdx.x;
    if (tid == 0) {
        const uint32_t bars = sb + (bid < NENG ? E_BAR : SM_BAR);
        if ((sb & 0xffffff) != SM_BASE) __trap();
        TV(0, 126, 0, gtl()); TS(0, 126, 1);
        sts32(bars + 388, 1);
        if (bid < NENG) sts32(sb + E_REDO, 0);
        sts32(bars + 384, *(volatile uint32_t*)&g_epoch);
        for (int i = 0; i < 11; i++) mbar_init(bars + i * 8, 1);
        mbar_init(bars + B_QK * 8, 8); mbar_init(bars + B_V * 8, 4); mbar_init(bars + B_OM * 8, 4);
        mbar_init(bars + B_E01 * 8, 8); mbar_init(bars + B_TF * 8, 24);
        for (int i = 0; i < 8; i++) mbar_init(bars + (B_EMPTY + i) * 8, 8);
        mbar_init(bars + B_PUB * 8, 8);
        if (bid < NENG) { mbar_init(bars + B_RF * 8, 8); mbar_init(bars + B_PD * 8, 12); mbar_init(bars + B_MF * 8, 8); mbar_init(bars + B_M * 8, 4); }
        for (int i = 0; i < 12; i++) mbar_init(bars + (B_R9 + i) * 8, 1);
        asm volatile("fence.mbarrier_init.release.cluster;" ::: "memory");
    }
    if (bid >= NENG) {
#pragma unroll 1
        for (int v = (bid - NENG) * NTHREADS + tid; v < (2 * LAG + (LAG < RING ? LAG + 1 : RING)) * 2304; v += (NGRID - NENG) * NTHREADS) {
            const int im = v / 2304, o = (v % 2304 >> 8) * 8192 + (v & 255) * 16;
            stg128((im < LAG ? g_xe + im * XIMG + 4096 : im < 2 * LAG ? g_xe + (im - LAG + NSEG) * XIMG : g_xf + (im - 2 * LAG) * XIMG + 4096) + o, make_uint4(0, 0, 0, 0));
        }
    }
    __syncthreads();
    if (bid < NENG) {
        cluster_arrive();
        if (wg == 0) { reg_inc<240>(); engine_a(P, sb); }
        else if (wg == 1) { reg_inc<200>(); engine_b(P, sb); }
        else { reg_dec<64>(); engine_c(P, sb); }
        TV(0, 126, 2, gtl()); TS(0, 126, 3);
        cluster_sync_all();
    } else if (bid < CTA_WO) {
        const int idx = bid - CTA_F1;
        if (wg < 2) { NOG; reg_inc<92 + 4 * F1_NR>(); stage_consumer<ST_F1, 0>(P, sb, idx, wg); }
        else {
            reg_dec<504 - 2 * (92 + 4 * F1_NR)>();
            const int w = __shfl_sync(~0u, (fresh_tid() >> 5) & 3, 0);
            if (w == 0) {
                NOG;
                stage_producer<ST_F1>(P, sb, idx);
            } else {
                if ((tid & 31) == 0) red_add_u32(g_flag[F_DONE][0], 1);
                ln_first(P, (w - 1) * NF1 + idx, LN0_SPLIT, 3 * NF1);
                if (idx < 32) {
                    const uint32_t epoch = __shfl_sync(~0u, lds32(sb + SM_EPOCH), 0);
                    uint32_t ph = 0;
#pragma unroll 1
                    for (int j = w == 3 ? LAG : 0; j < (w == 3 ? NSEG : NSTEP); j++) {
                        if (w == 3) mbar_wait(sb + SM_BAR + B_R9 * 8, (j - LAG) & 1);
                        ln_job(P, w == 2, j, w == 3, idx, epoch, sb + StageMap<ST_F1>::ROWS + (w - 1) * 6912, sb + SM_BAR + (B_R9 + w) * 8, ph);
                        if (w == 1 && j >= LAG && elect()) mbar_arrive(sb + SM_BAR + B_R9 * 8);
                    }
                    TV(320, 126, 2, gtl());
                }
                return;
            }
        }
    } else if (bid < CTA_SP) {
NOG;
        if (bid < CTA_F2) stage_split<ST_WO>(P, sb, wg, bid - CTA_WO);
        else stage_split<ST_F2>(P, sb, wg, bid - CTA_F2);
    } else {
        const int w = (bid - CTA_SP) * 12 + (tid >> 5);
        if (bid == CTA_SP && tid < NSTEP) red_add_u32(g_flag[F_XE][tid], 96 - 32 * ((tid < NSEG) + (tid >= LAG) + (tid > 2 * LAG + 1)));
        ln_first(P, LN0_SPLIT + w, S_TOK, 24);
        const uint32_t e1 = lds32(sb + SM_EPOCH) + 1;
        uint32_t ph = 0;
#pragma unroll 1
        for (int item = (LAG + 1) * 32 + w; item < (NSEG + 1) * 32; item += 24) {
            ln_job(P, 1, item >> 5, 1, item & 31, e1 - 1, sb + (tid >> 5) * 6912, sb + SM_BAR + (B_R9 + (tid >> 5)) * 8, ph);
        }
        TV(0, 126, 2, gtl()); TS(0, 126, 3);
        if (w == 23 && (tid & 31) == 0) {
            int n = 0;
            while ((int)(ld_rlx(g_flag[F_DONE][0]) - e1 * (CTA_SP * 12)) < 0) { SPIN_CHECK(n, 8); }
        }
        return;
    }
    __syncwarp();
    if ((fresh_tid() & 31) == 0) red_add_u32(g_flag[F_DONE][0], 1);
}

typedef CUresult (*EncodeFn)(CUtensorMap*, CUtensorMapDataType, cuuint32_t, void*, const cuuint64_t*, const cuuint64_t*,
                             const cuuint32_t*, const cuuint32_t*, CUtensorMapInterleave, CUtensorMapSwizzle,
                             CUtensorMapL2promotion, CUtensorMapFloatOOBfill);

void make_map(EncodeFn enc, CUtensorMap* m, const void* p, int rows, int cols) {
    cuuint64_t dims[3] = {64, (cuuint64_t)rows, (cuuint64_t)(cols / 64)};
    cuuint64_t strides[2] = {(cuuint64_t)cols * 2, 128};
    cuuint32_t box[3] = {64, 16, 1};
    cuuint32_t es[3] = {1, 1, 1};
    enc(m, CU_TENSOR_MAP_DATA_TYPE_BFLOAT16, 3, (void*)p, dims, strides, box, es, CU_TENSOR_MAP_INTERLEAVE_NONE,
        CU_TENSOR_MAP_SWIZZLE_128B, PROMO, CU_TENSOR_MAP_FLOAT_OOB_FILL_NONE);
}

void make_map2(EncodeFn enc, CUtensorMap* m, void* p, int words, int rows, int bw, int br) {
    cuuint64_t dims[2] = {(cuuint64_t)words, (cuuint64_t)rows};
    cuuint64_t strides[1] = {(cuuint64_t)words * 4};
    cuuint32_t box[2] = {(cuuint32_t)bw, (cuuint32_t)br};
    cuuint32_t es[2] = {1, 1};
    enc(m, CU_TENSOR_MAP_DATA_TYPE_UINT32, 2, p, dims, strides, box, es, CU_TENSOR_MAP_INTERLEAVE_NONE,
        CU_TENSOR_MAP_SWIZZLE_NONE, CU_TENSOR_MAP_L2_PROMOTION_NONE, CU_TENSOR_MAP_FLOAT_OOB_FILL_NONE);
}

}

extern "C" void kernel_launch(void* const* d_in, const int* in_sizes, int n_in, void* d_out, int out_size) {
    (void)in_sizes; (void)n_in; (void)out_size;
    static EncodeFn enc = nullptr;
    static void* rs = nullptr;
    if (!enc) {
        void* fn = nullptr;
        cudaDriverEntryPointQueryResult qr;
        cudaGetDriverEntryPoint("cuTensorMapEncodeTiled", &fn, cudaEnableDefault, &qr);
        enc = (EncodeFn)fn;
        cudaGetSymbolAddress(&rs, g_rs);
        cudaFuncSetAttribute(fused_kernel, cudaFuncAttributeMaxDynamicSharedMemorySize, SM_TOTAL);
    }
    Params P;
    make_map(enc, &P.tmWq, d_in[2], DM, 4096);
    make_map(enc, &P.tmWk, d_in[3], DM, 4096);
    make_map(enc, &P.tmWv, d_in[4], DM, 4096);
    make_map(enc, &P.tmWo, d_in[5], 4096, DM);
    make_map(enc, &P.tmW1, d_in[8], DM, FF);
    make_map(enc, &P.tmW3, d_in[9], DM, FF);
    make_map(enc, &P.tmW2, d_in[10], FF, DM);
    make_map2(enc, &P.tmRs, rs, 5120, 64, 16, 32);
    make_map2(enc, &P.tmR9, rs, 2560, 128, 4, 64);
    P.d128 = mkdesc(0, 1024, 1024, 1);
    P.d64 = mkdesc(0, 16, 512, 2);
    P.dX[0] = P.dX[1] = P.dX[2] = P.dX[3] = P.dX[4] = P.dX[5] = P.d128;
    P.dXk = P.dWk = P.d128 + E_WK / 16;
    P.dWo = P.d128 + E_WO / 16;
    P.dMq = P.dMq2 = P.dMk = P.dMv = mkdesc(E_MEM, 128, 1024, 0);
    P.dOm = mkdesc(E_OM, 16, 2048, 1);
    P.dQ = mkdesc(E_QX, 128, TG, 0);
    P.dK = mkdesc(E_KX, 128, 2 * TG, 0);
    P.zero = 0;
    P.x = (const bf16*)d_in[0];
    P.mem0 = (const bf16*)d_in[1];
    P.out = (bf16*)d_out;
    fused_kernel<<<NGRID, NTHREADS, SM_TOTAL>>>(P);
}
```

```cpp
#include <cuda_runtime.h>
#include <cuda_bf16.h>
#include <cuda.h>
#include <stdint.h>

typedef __nv_bfloat16 bf16;

namespace {

constexpr int S_TOK = 2048, DM = 576, NH = 32, FF = 4608, NSEG = 64;
#define LAG 7
#define RING 8
#define RB 4
static_assert(RING > LAG && (RING & (RING - 1)) == 0, "ring slots are only protected by the dataflow cycle");
constexpr int NSTEP = NSEG + LAG;
constexpr int NENG = 64, NF1 = 36, NWO = 15, NF2 = 15, NGRID = 132;
constexpr int CTA_F1 = NENG, CTA_WO = CTA_F1 + NF1, CTA_F2 = CTA_WO + NWO, CTA_SP = CTA_F2 + NF2;
constexpr int NTHREADS = 384;
constexpr int XIMG = 9 * 8192;
constexpr int XE_COUNT = 96 + NWO;
constexpr int LN0_SPLIT = 1088;
#define RS_DELAY 400
#define RS_SKEW 100
#define RS_DELAY0 500
#define AG_DELAY 150
#define GB1 1
#define GB2 3
#define WIB_AT 1
#define GB3 1
#define LATE_WAIT 600
#define LATE_MUL 7
#define X7_DELAY 0
#define F1_NR 29
#define F1_SLOTS 4
#define CFENCE fence_async_smem()
#define KLOOP 3
#define LATE_NS 950
#define B_EARLY 1
#define S0Q 8
#define S0V 35
#define XS 0
#define XSEQ W(0) Q(0) Q(1) K(0) K(1) C W(2) B(2) E B(3) C W(4) B(4) M W(5) B(5) B(6) C W(7) B(7) T K(8) C Q(8) C
#define KEARLY 1
#define PROMO CU_TENSOR_MAP_L2_PROMOTION_L2_128B
#define NARROW 1
#define RB_DELAY 0
#define X4_AT 1
#define RS_AT 3080
#define AG_AT 1350
#define W_POL EVICT_FIRST
#define O_POL EVICT_FIRST
#define G_DELAY 12000
#define WO_DELAY 3000
#define WO_PACE 0
#define F1_PACE 500
#define F2_PACE 500
constexpr int SPIN_LIMIT = 4000000;

enum { F_XE = 0, F_XF, F_PW, F_PF, F_L2, F_O, F_H = F_O + 5, F_DONE = F_H + 5, F_COUNT };
__device__ uint32_t g_flag[F_COUNT][NSTEP + 2][8];
__device__ uint32_t g_epoch;
__device__ unsigned long long g_latest;
__device__ __align__(1024) uint8_t g_xe[NSTEP * XIMG];
__device__ __align__(1024) uint8_t g_xf[RING * XIMG];
__device__ __align__(1024) uint8_t g_o[RB * 64 * 8192];
__device__ __align__(1024) uint8_t g_h[RB * FF * 128];
__device__ __align__(1024) uint8_t g_part[2][RB * 64 * 5 * 1152];
__device__ __align__(1024) uint8_t g_x1[RING * 64 * 1152];
__device__ __align__(1024) uint8_t g_res[2][S_TOK * 1152];
__device__ __align__(1024) uint8_t g_rs[2 * NENG * 10240];
__device__ __align__(1024) uint8_t g_ag[2 * 18432];

struct Params {
    CUtensorMap tmWq, tmWk, tmWv, tmWo, tmW1, tmW3, tmW2, tmRs, tmR9;
    uint64_t d128, d64, dOm, dQ, dK, dX[6], dXk, dMq, dMq2, dMk, dMv, dWk, dWo;
    uint32_t zero;
    const bf16* x;
    const bf16* mem0;
    bf16* out;
};

constexpr int SM_TOTAL = 232448;
constexpr int SM_BAR = SM_TOTAL - 512;
constexpr int KRQ = 34, KRV = 35;
constexpr int E_WK = 0;
constexpr int E_WO = E_WK + 36 * 2048;
constexpr int E_WQ = E_WO + 36 * 2048;
constexpr int E_WV = E_WQ + (36 - KRQ) * 2048;
constexpr int E_RING = E_WV + (36 - KRV) * 2048;
constexpr int E_MEM = E_RING + 2 * 8192;
constexpr int TG = 2064;
constexpr int E_T = E_MEM + 18432;
constexpr int E_QX = E_T, E_QM = E_T, E_KX = E_T + 3 * TG, E_KM = E_T + 11 * TG, E_VX = E_T + 8 * TG, E_VM = E_T + 13 * TG;
constexpr int E_RS = E_T + 16384;
constexpr int E_BAR = E_T + 15 * TG;
constexpr int E_R2 = SM_TOTAL - 8192;
constexpr int E_OM = E_R2 - 4096;
constexpr int SG = 3104, E_OUT = SM_TOTAL - 3 * SG - 3072;
static_assert(E_BAR + 544 <= E_OUT && E_RING % 1024 == 0 && E_MEM % 1024 == 0 && E_OM % 1024 == 0 && E_T % 1024 == 0, "engine smem");
constexpr int E_ST1 = 19;
__host__ __device__ constexpr int e_stage(int j) { return j < 32 ? E_RING + j * 2048 : E_OM + (j - 32) * 2048; }
static_assert(E_RING + 32 * 2048 <= E_BAR && 2 * E_ST1 <= 38, "staging");
__host__ __device__ constexpr int x_slot(int c) {
    return c < 2 ? E_RING + c * 8192 : c < 4 ? E_MEM + (c - 2) * 8192 : c == 4 ? E_R2 : c < 7 ? E_T + (c - 5) * 8192 : E_RING + (c - 7) * 8192;
}
enum { B_XF = 0, B_WL = 9, B_WS, B_QK, B_V, B_OM, B_E01, B_TF, B_RF = 1, B_PD = 3, B_MF = 6, B_M = 8, B_R9 = 49, B_RS = B_R9 + 2, B_ML = B_RS + 4, B_WO, B_SD, B_FULL = 0, B_EMPTY = 16, B_PUB = 32 };
enum { NB_ALL = 1, NB_QKI, NB_SI, NB_PVI, NB_WIA, NB_WIB, NB_XI, NB_C, NB_WG0, NB_WG1 };
constexpr int SM_EPOCH = SM_BAR + 384, E_EPOCH = E_BAR + 384, E_ONE = E_BAR + 388, E_INV = E_BAR + 464, E_REDO = E_BAR + 528;

#define SPIN_CHECK(n, code) asm volatile("{.reg .pred p; setp.gt.s32 p, %0, %1; @p st.global.u32 [%2], %0;}" :: "r"(++(n)), "n"(SPIN_LIMIT), "l"(0ull))

#define EV(thr, k, v)
#define ES(thr, k)
#define EFLUSH(step)
#define TS(thr, step, k)
#define TV(thr, step, k, v)

__device__ __forceinline__ uint32_t smem_u32(const void* p) { return (uint32_t)__cvta_generic_to_shared(p); }
__device__ __forceinline__ uint32_t mapa(uint32_t a, uint32_t r) {
    uint32_t o; asm("mapa.shared::cluster.u32 %0, %1, %2;" : "=r"(o) : "r"(a), "r"(r)); return o;
}
__device__ __forceinline__ void mbar_init(uint32_t b, uint32_t cnt) {
    asm volatile("mbarrier.init.shared::cta.b64 [%0], %1;" :: "r"(b), "r"(cnt) : "memory");
}
__device__ __forceinline__ void mbar_arrive(uint32_t b) {
    asm volatile("mbarrier.arrive.shared::cta.b64 _, [%0];" :: "r"(b) : "memory");
}
__device__ __forceinline__ void mbar_arrive_remote(uint32_t b) {
    asm volatile("mbarrier.arrive.relaxed.cluster.shared::cluster.b64 _, [%0];" :: "r"(b) : "memory");
}
__device__ __forceinline__ void mbar_expect(uint32_t b, uint32_t bytes) {
    asm volatile("mbarrier.arrive.expect_tx.shared::cta.b64 _, [%0], %1;" :: "r"(b), "r"(bytes) : "memory");
}
#define RETRY(n, code) n = 1
#define MBAR_WAIT(SEM) asm volatile("{.reg .pred p; W: mbarrier.try_wait.parity" SEM ".shared::cta.b64 p, [%0], %1; @!p bra W;}" :: "r"(b), "r"(par) : "memory")
__device__ __forceinline__ void mbar_wait(uint32_t b, uint32_t par) { MBAR_WAIT(""); }
__device__ __forceinline__ void mbar_wait_cl(uint32_t b, uint32_t par) {
    MBAR_WAIT(".relaxed.cluster");
    asm volatile("fence.acquire.sync_restrict::shared::cluster.cluster;" ::: "memory");
}
__device__ __forceinline__ void nbar_sync(int id, int n) { asm volatile("bar.sync %0, %1;" :: "r"(id), "r"(n) : "memory"); }
__device__ __forceinline__ void nbar_arrive(int id, int n) { asm volatile("bar.arrive %0, %1;" :: "r"(id), "r"(n) : "memory"); }
__device__ __forceinline__ uint32_t nbar_any(int id, int n, uint32_t v) {
    uint32_t r;
    asm volatile("{.reg .pred p, q; setp.ne.u32 p, %3, 0; bar.red.or.pred q, %1, %2, p; selp.u32 %0, 1, 0, q;}" : "=r"(r) : "r"(id), "r"(n), "r"(v) : "memory");
    return r;
}
__device__ __forceinline__ uint32_t clock_after(uint32_t zero) {
    uint32_t t;
    asm volatile("{.reg .pred p; setp.eq.u32 p, %1, 0; mov.u32 %0, 0; @p mov.u32 %0, %%clock;}" : "=r"(t) : "r"(zero) : "memory");
    return t;
}
__device__ __forceinline__ void cluster_sync_all() {
    asm volatile("barrier.cluster.arrive.release.aligned; barrier.cluster.wait.acquire.aligned;" ::: "memory");
}
__device__ __forceinline__ void cluster_arrive() { asm volatile("barrier.cluster.arrive.relaxed.aligned;" ::: "memory"); }
__device__ __forceinline__ void cluster_wait() { asm volatile("barrier.cluster.wait.aligned;" ::: "memory"); }
__device__ __forceinline__ void fence_async_smem() { asm volatile("fence.proxy.async.shared::cta;" ::: "memory"); }
__device__ __forceinline__ void fence_async_glb() { asm volatile("fence.proxy.async.global;" ::: "memory"); }
__device__ __forceinline__ void fence_rel_gpu() { asm volatile("fence.release.gpu;" ::: "memory"); }
__device__ __forceinline__ void fence_acq_gpu() { asm volatile("fence.acquire.gpu;" ::: "memory"); }
__device__ __forceinline__ int fresh_tid() { int t; asm volatile("mov.u32 %0, %%tid.x;" : "=r"(t)); return t; }
__device__ __forceinline__ int fresh_bid() { int t; asm volatile("mov.u32 %0, %%ctaid.x;" : "=r"(t)); return t; }
__device__ __forceinline__ uint32_t keep(uint32_t v) { asm volatile("" : "+r"(v)); return v; }
__device__ __forceinline__ uint32_t opaque(uint32_t v) { return __shfl_xor_sync(~0u, v, 0); }
__device__ __forceinline__ bool elect() {
    uint32_t p; asm volatile("{.reg .pred p; elect.sync _|p, 0xffffffff; selp.u32 %0, 1, 0, p;}" : "=r"(p)); return p;
}
__device__ __forceinline__ uint32_t clock32() { uint32_t t; asm volatile("mov.u32 %0, %%clock;" : "=r"(t) :: "memory"); return t; }
__device__ __forceinline__ void red_add_u32(uint32_t* p, uint32_t v) {
    asm volatile("red.relaxed.gpu.global.add.u32 [%0], %1;" :: "l"(p), "r"(v) : "memory");
}
__device__ __forceinline__ uint32_t ld_rlx(const uint32_t* p) {
    uint32_t v; asm volatile("ld.relaxed.gpu.global.u32 %0, [%1];" : "=r"(v) : "l"(p) : "memory"); return v;
}
__device__ __forceinline__ void st_rlx128(void* p, uint4 v) {
    asm volatile("{.reg .b128 r; .reg .b64 a, b; mov.b64 a, {%1,%2}; mov.b64 b, {%3,%4}; mov.b128 r, {a, b}; st.relaxed.gpu.global.b128 [%0], r;}"
                 :: "l"(p), "r"(v.x), "r"(v.y), "r"(v.z), "r"(v.w) : "memory");
}
__device__ __forceinline__ void st_rlx64(void* p, uint32_t a, uint32_t b) {
    asm volatile("{.reg .b64 r; mov.b64 r, {%1,%2}; st.relaxed.gpu.global.b64 [%0], r;}" :: "l"(p), "r"(a), "r"(b) : "memory");
}
__device__ __forceinline__ void st_rlx32(void* p, uint32_t v) { asm volatile("st.relaxed.gpu.global.u32 [%0], %1;" :: "l"(p), "r"(v) : "memory"); }
__device__ __forceinline__ uint32_t xor_or(uint32_t a, uint32_t b, uint32_t t) {
    uint32_t d; asm("lop3.b32 %0, %1, %2, %3, 0x7E;" : "=r"(d) : "r"(a), "r"(b), "r"(t)); return d;
}
__device__ __forceinline__ uint32_t tagged(uint32_t w, uint32_t m, uint32_t tag) {
    uint32_t d; asm("lop3.b32 %0, %1, %2, %3, 0xB8;" : "=r"(d) : "r"(w), "r"(m), "r"(tag)); return d;
}
__device__ __forceinline__ uint32_t or3(uint32_t a, uint32_t b, uint32_t c) {
    uint32_t d; asm("lop3.b32 %0, %1, %2, %3, 0xFE;" : "=r"(d) : "r"(a), "r"(b), "r"(c)); return d;
}
__device__ __forceinline__ uint32_t or_bit0(uint32_t a, uint32_t b) {
    uint32_t d; asm("lop3.b32 %0, %1, %2, 1, 0xA8;" : "=r"(d) : "r"(a), "r"(b)); return d;
}
__device__ __forceinline__ uint4 ld_l2_128(const void* p) {
    uint4 v;
    asm volatile("ld.relaxed.gpu.global.v4.u32 {%0,%1,%2,%3}, [%4];" : "=r"(v.x), "=r"(v.y), "=r"(v.z), "=r"(v.w) : "l"(p) : "memory");
    return v;
}
__device__ __forceinline__ void stg128(void* p, uint4 v) {
    asm volatile("st.global.v4.b32 [%0], {%1,%2,%3,%4};" :: "l"(p), "r"(v.x), "r"(v.y), "r"(v.z), "r"(v.w) : "memory");
}
__device__ __forceinline__ void stg64(void* p, uint32_t a, uint32_t b) {
    asm volatile("st.global.v2.b32 [%0], {%1,%2};" :: "l"(p), "r"(a), "r"(b) : "memory");
}
__device__ __forceinline__ void st_async128(uint32_t a, uint4 v, uint32_t mb) {
    asm volatile("st.async.shared::cluster.mbarrier::complete_tx::bytes.v4.b32 [%0], {%1,%2,%3,%4}, [%5];"
                 :: "r"(a), "r"(v.x), "r"(v.y), "r"(v.z), "r"(v.w), "r"(mb) : "memory");
}
__device__ __forceinline__ void st_async32(uint32_t a, uint32_t v, uint32_t mb) {
    asm volatile("st.async.shared::cluster.mbarrier::complete_tx::bytes.b32 [%0], %1, [%2];" :: "r"(a), "r"(v), "r"(mb) : "memory");
}
__device__ __forceinline__ void sts128(uint32_t a, uint4 v) {
    asm volatile("st.shared.v4.b32 [%0], {%1,%2,%3,%4};" :: "r"(a), "r"(v.x), "r"(v.y), "r"(v.z), "r"(v.w) : "memory");
}
__device__ __forceinline__ void sts32(uint32_t a, uint32_t v) { asm volatile("st.shared.b32 [%0], %1;" :: "r"(a), "r"(v) : "memory"); }
__device__ __forceinline__ uint32_t lds32(uint32_t a) { uint32_t v; asm volatile("ld.shared.b32 %0, [%1];" : "=r"(v) : "r"(a) : "memory"); return v; }
__device__ __forceinline__ uint2 lds64(uint32_t a) {
    uint2 v; asm volatile("ld.shared.v2.b32 {%0,%1}, [%2];" : "=r"(v.x), "=r"(v.y) : "r"(a) : "memory"); return v;
}
__device__ __forceinline__ uint4 lds128(uint32_t a) {
    uint4 v; asm volatile("ld.shared.v4.b32 {%0,%1,%2,%3}, [%4];" : "=r"(v.x), "=r"(v.y), "=r"(v.z), "=r"(v.w) : "r"(a) : "memory"); return v;
}
__device__ __forceinline__ void bulk_g2s(uint32_t dst, const void* src, uint32_t bytes, uint32_t mb) {
    asm volatile("cp.async.bulk.shared::cluster.global.mbarrier::complete_tx::bytes [%0], [%1], %2, [%3];"
                 :: "r"(dst), "l"(src), "r"(bytes), "r"(mb) : "memory");
}
__device__ __forceinline__ void bulk_s2peer(uint32_t dst, uint32_t src, uint32_t bytes, uint32_t mb) {
    asm volatile("cp.async.bulk.shared::cluster.shared::cta.mbarrier::complete_tx::bytes [%0], [%1], %2, [%3];"
                 :: "r"(dst), "r"(src), "r"(bytes), "r"(mb) : "memory");
}
__device__ __forceinline__ void tma_2d(uint32_t dst, const CUtensorMap* tm, int x, int y, uint32_t mb) {
    asm volatile("cp.async.bulk.tensor.2d.shared::cluster.global.mbarrier::complete_tx::bytes [%0], [%1, {%2,%3}], [%4];"
                 :: "r"(dst), "l"(tm), "r"(x), "r"(y), "r"(mb) : "memory");
}
constexpr uint64_t EVICT_FIRST = 0x12F0000000000000ull, EVICT_NORMAL = 0x1000000000000000ull;
__device__ __forceinline__ void tma_w(uint32_t dst, const CUtensorMap* tm, int ks, int grp, uint32_t mb) {
    asm volatile("cp.async.bulk.tensor.3d.shared::cluster.global.mbarrier::complete_tx::bytes.L2::cache_hint [%0], [%1, {%2,%3,%4}], [%5], %6;"
                 :: "r"(dst), "l"(tm), "r"(0), "r"(ks * 16), "r"(grp), "r"(mb), "l"(W_POL) : "memory");
}
__device__ __forceinline__ void stg64_last(void* p, uint32_t a, uint32_t b) {
    asm volatile("st.global.L2::cache_hint.v2.b32 [%0], {%1,%2}, %3;" :: "l"(p), "r"(a), "r"(b), "l"(O_POL) : "memory");
}
__device__ __forceinline__ void ldsm4t(uint32_t* r, uint32_t a) {
    asm volatile("ldmatrix.sync.aligned.m8n8.x4.trans.shared.b16 {%0,%1,%2,%3}, [%4];"
                 : "=r"(r[0]), "=r"(r[1]), "=r"(r[2]), "=r"(r[3]) : "r"(a) : "memory");
}
__device__ __forceinline__ uint32_t movm(uint32_t a) {
    uint32_t d; asm volatile("movmatrix.sync.aligned.m8n8.trans.b16 %0, %1;" : "=r"(d) : "r"(a)); return d;
}
__device__ __forceinline__ uint32_t pack2(float lo, float hi) {
    uint32_t d; asm("cvt.rn.bf16x2.f32 %0, %1, %2;" : "=r"(d) : "f"(hi), "f"(lo)); return d;
}
__device__ __forceinline__ float bf_lo(uint32_t w) { return __uint_as_float(w << 16); }
__device__ __forceinline__ float bf_hi(uint32_t w) { return __uint_as_float(w & 0xffff0000u); }
__device__ __forceinline__ float ex2(float x) { float y; asm("ex2.approx.ftz.f32 %0, %1;" : "=f"(y) : "f"(x)); return y; }
__device__ __forceinline__ float rcp(float x) { float y; asm("rcp.approx.ftz.f32 %0, %1;" : "=f"(y) : "f"(x)); return y; }
__device__ __forceinline__ void spin_cycles(int c) {
    uint32_t t0, t1;
    asm volatile("mov.u32 %0, %%clock;" : "=r"(t0));
    do { asm volatile("mov.u32 %0, %%clock;" : "=r"(t1)); } while ((int)(t1 - t0) < c);
}
template <int N> __device__ __forceinline__ void reg_inc() { asm volatile("setmaxnreg.inc.sync.aligned.u32 %0;" :: "n"(N)); }
template <int N> __device__ __forceinline__ void reg_dec() { asm volatile("setmaxnreg.dec.sync.aligned.u32 %0;" :: "n"(N)); }

__device__ __forceinline__ void pin(const Params& P, uint32_t v) {
    asm volatile("{.reg .pred p; .reg .b32 t; and.b32 t, %0, %1; setp.ne.u32 p, t, 0; @p st.shared.u32 [%0], t;}" :: "r"(v), "r"(P.zero) : "memory");
    __syncwarp();
}
__device__ __forceinline__ void flag_poll(const uint32_t* f, uint32_t target) {
    int n = 0;
    while ((int)(ld_rlx(f) - target) < 0) {
        SPIN_CHECK(n, (int)(f - &g_flag[0][0][0]) / 8);
    }
}
__device__ __forceinline__ void flag_signal_after(const Params& P, uint32_t* f, uint32_t loaded) { red_add_u32(f, (loaded & P.zero) + 1); }
__device__ __forceinline__ void flag_signal(uint32_t* f) {
    fence_rel_gpu();
    red_add_u32(f, 1);
}

constexpr uint32_t SM_BASE = 1024;
__host__ __device__ constexpr uint64_t mkdesc(uint32_t off, uint32_t lbo, uint32_t sbo, uint32_t swz) {
    return (uint64_t)((SM_BASE + off) >> 4) | ((uint64_t)(lbo >> 4) << 16) | ((uint64_t)(sbo >> 4) << 32) | ((uint64_t)swz << 62);
}
__device__ __forceinline__ void dmove(uint64_t& d, int delta) { asm volatile("add.s64 %0, %0, %1;" : "+l"(d) : "l"((long long)delta)); }
__device__ __forceinline__ void wg_fence() { asm volatile("wgmma.fence.sync.aligned;" ::: "memory"); }
__device__ __forceinline__ void wg_commit() { asm volatile("wgmma.commit_group.sync.aligned;" ::: "memory"); }
template <int N> __device__ __forceinline__ void wg_wait() { asm volatile("wgmma.wait_group.sync.aligned %0;" :: "n"(N) : "memory"); }

#define F4(c, d, o) c(d[o]), c(d[o + 1]), c(d[o + 2]), c(d[o + 3])
#define F8(c, d, o) F4(c, d, o), F4(c, d, o + 4)
#define F32(c, d, o) F8(c, d, o), F8(c, d, o + 8), F8(c, d, o + 16), F8(c, d, o + 24)
#define L8 "%0,%1,%2,%3,%4,%5,%6,%7"
#define L16 L8 ",%8,%9,%10,%11,%12,%13,%14,%15"
#define L20 L16 ",%16,%17,%18,%19"
#define L32 L20 ",%20,%21,%22,%23,%24,%25,%26,%27,%28,%29,%30,%31"
#define L64 L32 ",%32,%33,%34,%35,%36,%37,%38,%39,%40,%41,%42,%43,%44,%45,%46,%47,%48,%49,%50,%51,%52,%53,%54,%55,%56,%57,%58,%59,%60,%61,%62,%63"
#define O8(c) F8(c, d, 0)
#define O16(c) F8(c, d, 0), F8(c, d, 8)
#define O20(c) F8(c, d, 0), F8(c, d, 8), F4(c, d, 16)
#define O32(c) F32(c, d, 0)
#define O64(c) F32(c, d, 0), F32(c, d, 32)
#define WG_BOTH(TXT_PRE, TXT_POST, OUTS, ...)                                                   \
    if (acc > 0) asm volatile(TXT_PRE "1" TXT_POST : OUTS("+f") : __VA_ARGS__);                 \
    else if (acc < 0) asm volatile(TXT_PRE "0" TXT_POST : OUTS("+f") : __VA_ARGS__);            \
    else asm volatile(TXT_PRE "0" TXT_POST : OUTS("=f") : __VA_ARGS__)
#define AREGS "r"(a[0]), "r"(a[1]), "r"(a[2]), "r"(a[3])
template <int TB> __device__ __forceinline__ void wg_rs16(float* d, const uint32_t* a, uint64_t db, int acc) {
    WG_BOTH("wgmma.mma_async.sync.aligned.m64n16k16.f32.bf16.bf16 {" L8 "}, {%8,%9,%10,%11}, %12, ", ", 1, 1, %13;", O8, AREGS, "l"(db), "n"(TB));
}
template <int TB> __device__ __forceinline__ void wg_ss16(float* d, uint64_t da, uint64_t db, int acc) {
    WG_BOTH("wgmma.mma_async.sync.aligned.m64n16k16.f32.bf16.bf16 {" L8 "}, %8, %9, ", ", 1, 1, 1, %10;", O8, "l"(da), "l"(db), "n"(TB));
}
template <int TB> __device__ __forceinline__ void wg_rs32(float* d, const uint32_t* a, uint64_t db, int acc) {
    WG_BOTH("wgmma.mma_async.sync.aligned.m64n32k16.f32.bf16.bf16 {" L16 "}, {%16,%17,%18,%19}, %20, ", ", 1, 1, %21;", O16, AREGS, "l"(db), "n"(TB));
}
template <int TB> __device__ __forceinline__ void wg_ss32(float* d, uint64_t da, uint64_t db, int acc) {
    WG_BOTH("wgmma.mma_async.sync.aligned.m64n32k16.f32.bf16.bf16 {" L16 "}, %16, %17, ", ", 1, 1, 1, %18;", O16, "l"(da), "l"(db), "n"(TB));
}
template <int TB> __device__ __forceinline__ void wg_ss40(float* d, uint64_t da, uint64_t db, int acc) {
    WG_BOTH("wgmma.mma_async.sync.aligned.m64n40k16.f32.bf16.bf16 {" L20 "}, %20, %21, ", ", 1, 1, 1, %22;", O20, "l"(da), "l"(db), "n"(TB));
}
template <int TB> __device__ __forceinline__ void wg_rs64(float* d, const uint32_t* a, uint64_t db, int acc) {
    WG_BOTH("wgmma.mma_async.sync.aligned.m64n64k16.f32.bf16.bf16 {" L32 "}, {%32,%33,%34,%35}, %36, ", ", 1, 1, %37;", O32, AREGS, "l"(db), "n"(TB));
}
template <int TB> __device__ __forceinline__ void wg_ss64(float* d, uint64_t da, uint64_t db, int acc) {
    WG_BOTH("wgmma.mma_async.sync.aligned.m64n64k16.f32.bf16.bf16 {" L32 "}, %32, %33, ", ", 1, 1, 1, %34;", O32, "l"(da), "l"(db), "n"(TB));
}
template <int TB> __device__ __forceinline__ void wg_rs128(float* d, const uint32_t* a, uint64_t db, int acc) {
    WG_BOTH("wgmma.mma_async.sync.aligned.m64n128k16.f32.bf16.bf16 {" L64 "}, {%64,%65,%66,%67}, %68, ", ", 1, 1, %69;", O64, AREGS, "l"(db), "n"(TB));
}
__device__ __forceinline__ uint32_t frag_addr(uint32_t base) {
    const int tid = threadIdx.x, i = tid & 7, j = (tid >> 3) & 3, warp = (tid >> 5) & 3;
    return base + ((j >> 1) * 8 + i) * 128 + ((((warp << 1) + (j & 1)) ^ i) << 4);
}

constexpr float SM_SCALE = 0.08838834764831845f;
constexpr float LOG2E = 1.4426950408889634f;

__device__ __forceinline__ void add8(float* f, uint4 a) {
    f[0] += bf_lo(a.x); f[1] += bf_hi(a.x); f[2] += bf_lo(a.y); f[3] += bf_hi(a.y);
    f[4] += bf_lo(a.z); f[5] += bf_hi(a.z); f[6] += bf_lo(a.w); f[7] += bf_hi(a.w);
}
__device__ __forceinline__ void sum_row(uint4* xw, const uint8_t* part, const uint8_t* res, uint32_t tag, uint32_t buf, uint32_t mb, uint32_t& ph, int l) {
    int n = 0;
#pragma unroll 1
    while (true) {
        if (elect()) { mbar_expect(mb, 6 * 1152); bulk_g2s(buf, part, 5 * 1152, mb); bulk_g2s(buf + 5 * 1152, res, 1152, mb); }
        SPIN_CHECK(n, 7);
        mbar_wait(mb, ph);
        ph ^= 1;
        uint32_t bad = 0;
#pragma unroll
        for (int k = 0; k < 3; k++) {
            uint4 a[6];
#pragma unroll
            for (int j = 0; j < 6; j++) a[j] = lds128(buf + l * 16 + k * 384 + j * 1152);
            float f[8] = {0.f, 0.f, 0.f, 0.f, 0.f, 0.f, 0.f, 0.f};
#pragma unroll
            for (int j = 0; j < 6; j++) add8(f, a[j]);
            bad = or3(bad | (a[4].x ^ tag), xor_or(a[0].x, a[1].x, tag), xor_or(a[2].x, a[3].x, tag));
            xw[k] = make_uint4(pack2(f[0], f[1]), pack2(f[2], f[3]), pack2(f[4], f[5]), pack2(f[6], f[7]));
        }
        if (!__any_sync(~0u, bad & 1)) break;
    }
}
__device__ __forceinline__ void ln_row(const Params& P, const uint4* xw, uint8_t* keep_at, uint8_t* img, int n, uint32_t* flag, int lane) {
    const int l = lane < 24 ? lane : 0;
    const float shift = bf_lo(__shfl_sync(~0u, xw[0].x, 0));
    float s = 0.f, q = 0.f;
#pragma unroll
    for (int k = 0; k < 3; k++) {
        float f[8] = {-shift, -shift, -shift, -shift, -shift, -shift, -shift, -shift};
        add8(f, xw[k]);
#pragma unroll
        for (int j = 0; j < 8; j++) { s += f[j]; q += f[j] * f[j]; }
    }
    if (lane >= 24) s = q = 0.f;
#pragma unroll
    for (int o = 16; o; o >>= 1) { s += __shfl_xor_sync(~0u, s, o); q += __shfl_xor_sync(~0u, q, o); }
    const float mean = s * (1.f / DM);
    const float rstd = rsqrtf(fmaxf(q * (1.f / DM) - mean * mean, 0.f) + 1e-5f), mu = shift + mean;
    const int row = ((n >> 1) & 3) * 8 + ((n >> 3) & 3) * 2 + (n & 33);
    img += row * 128;
    if (lane < 24) {
        uint8_t* d = img + (l >> 3) * 8192 + (l & 1) * 8;
        const uint32_t c0 = ((l & 6) ^ (row & 7)) << 4;
#define NRM(w) pack2((bf_lo(w) - mu) * rstd, (bf_hi(w) - mu) * rstd)
#pragma unroll
        for (int k = 0; k < 3; k++) {
            stg64(d + k * 24576 + c0, NRM(xw[k].x), NRM(xw[k].z));
            stg64(d + k * 24576 + (c0 ^ 16), NRM(xw[k].y), NRM(xw[k].w));
        }
#undef NRM
#pragma unroll
        for (int k = 0; k < 3; k++) stg128(keep_at + l * 16 + k * 384, xw[k]);
    }
    __syncwarp();
    const int j = lane < 18 ? lane : 0;
    const uint32_t v = ld_rlx((const uint32_t*)(j < 9 ? img + j * 8192 : keep_at + (j - 9) * 128));
    if (lane == 0) flag_signal_after(P, flag, v);
}
__device__ __forceinline__ void ln_first(const Params& P, int row0, int row1, int stride) {
    const int lane = threadIdx.x & 31, l = lane < 24 ? lane : 0;
#pragma unroll 1
    for (int tok = row0; tok < row1; tok += stride) {
        const uint8_t* src = (const uint8_t*)P.x + tok * 1152 + (l >> 1) * 32 + (l & 1) * 8;
        uint4 xw[3];
#pragma unroll
        for (int k = 0; k < 3; k++) {
            const uint2 a = __ldg((const uint2*)(src + k * 384)), b = __ldg((const uint2*)(src + k * 384 + 16));
            xw[k] = make_uint4(a.x, b.x, a.y, b.y);
        }
        ln_row(P, xw, g_res[0] + tok * 1152, g_xe + (tok >> 5) * XIMG, tok & 31, g_flag[F_XE][tok >> 5], lane);
    }
}
__device__ __forceinline__ void ln_job(const Params& P, int second, int j, int late, int r, uint32_t epoch, uint32_t buf, uint32_t mb, uint32_t& ph) {
#define LAYER (late | (j >= NSEG))
#define TOK ((j - (late & second) - LAYER * LAG) * 32 + r)
#define ROUND (j + (late & ~second))
#define X1 (g_x1 + ((ROUND & (RING - 1)) * 64 + late * 32 + r) * 1152)
    uint4 xw[3];
    {
        const uint32_t use = epoch * NSTEP + j;
        const int lane = fresh_tid() & 31;
        flag_poll(g_flag[F_PW + second][j], (epoch + 1) * NWO);
        fence_acq_gpu();
        fence_async_glb();
        TS(288, j, 10); TS(320, j, 13);
        sum_row(xw, g_part[second] + ((use & (RB - 1)) * 64 + (second ? late : LAYER) * 32 + r) * 5760, second ? X1 : g_res[LAYER] + TOK * 1152,
                ((use / RB) & 1) ^ 1, buf, mb, ph, lane < 24 ? lane : 0);
        TS(288, j, 11); TS(320, j, 14);
    }
    j = keep(j);
    const int lane = fresh_tid() & 31, l = lane < 24 ? lane : 0;
    if (second && lane == 0) red_add_u32(g_flag[F_L2][j], 1);
    if (second && LAYER) {
        if (lane < 24) {
            uint8_t* d = (uint8_t*)P.out + TOK * 1152 + (l >> 1) * 32 + (l & 1) * 8;
#pragma unroll
            for (int k = 0; k < 3; k++) { stg64_last(d + k * 384, xw[k].x, xw[k].z); stg64_last(d + k * 384 + 16, xw[k].y, xw[k].w); }
        }
        if (lane == 0 && j + LAG + 1 < NSTEP) red_add_u32(g_flag[F_XE][j + LAG + 1], 1);
    } else {
        ln_row(P, xw, second ? g_res[1] + TOK * 1152 : X1, second ? g_xe + (j + LAG) * XIMG : g_xf + (ROUND & (RING - 1)) * XIMG,
               (second | late) * 32 + r, second ? g_flag[F_XE][j + LAG] : g_flag[F_XF][ROUND], lane);
    }
    TS(288, j, 12); TS(320, j, 15);
#undef X1
#undef ROUND
#undef TOK
#undef LAYER
}

template <int KR, int WG>
__device__ __forceinline__ void load_wregs(uint32_t (&w)[KR][4], uint32_t sb) {
    const uint32_t base = frag_addr(sb);
    mbar_wait(sb + E_BAR + B_WL * 8, 0);
    TV(0, 126, 4, gtl());
#pragma unroll
    for (int ks = 0; ks < E_ST1; ks++) ldsm4t(w[ks], base + e_stage(WG * E_ST1 + ks));
    nbar_sync(NB_ALL, NTHREADS);
    mbar_wait(sb + E_BAR + B_WL * 8, 1);
    TV(0, 126, 5, gtl());
#pragma unroll
    for (int ks = E_ST1; ks < KR; ks++) ldsm4t(w[ks], base + e_stage(WG * E_ST1 + ks - E_ST1));
    nbar_sync(NB_XI, 256);
    cluster_wait();
    TV(0, 126, 6, gtl());
    mbar_wait(sb + E_BAR + B_WS * 8, 0);
    TV(0, 126, 7, gtl());
}
__host__ __device__ constexpr int m_pos(int tile) { return tile == 8 ? 0 : 1 + 2 * (tile & 3) + (tile >> 2); }
__host__ __device__ constexpr int m_off(int ks) { return m_pos(ks >> 2) * 128 + (ks & 3) * 16; }
template <int KR> struct Res {
    static constexpr int NS = 36 - KR, S0 = KR == KRQ ? S0Q : S0V;
    __host__ __device__ static constexpr bool ss(int ks) { return ks >= S0 && ks < S0 + NS; }
    __host__ __device__ static constexpr int reg(int ks) { return ks < S0 ? ks : ks < S0 + NS ? 0 : ks - NS; }
    __host__ __device__ static constexpr int step(int r) { return r < S0 ? r : r + NS; }
};
template <int KR, bool LEAD>
__device__ __forceinline__ void proj_mem(uint64_t dw, float* d, const uint32_t (&w)[KR][4], uint32_t wss) {
    using R = Res<KR>;
    dw += m_off(R::step(0));
    wg_fence();
#pragma unroll
    for (int j = 0; j < R::NS; j++) wg_ss16<1>(d, mkdesc(wss + j * 2048, 1024, 1024, 1), mkdesc(E_MEM, 128, 1024, 0) + m_off(R::S0 + j), j > 0);
#pragma unroll
    for (int r = 0; r < KR; r++) { wg_rs16<1>(d, w[r], dw, 1); if (r < KR - 1) dmove(dw, m_off(R::step(r + 1)) - m_off(R::step(r))); }
    wg_commit();
    if (LEAD) nbar_arrive(NB_QKI, NTHREADS);
}
struct Walk {
    uint64_t d;
    int at = -1;
    __device__ __forceinline__ uint64_t to(uint64_t base, int off) {
        if (at < 0) d = base + off; else if (off != at) dmove(d, off - at);
        at = off;
        return d;
    }
};
template <int KR, int WHAT>
__device__ __forceinline__ void proj_x(const Params& P, Walk* wk, float* d, float* dk, const uint32_t (&w)[KR][4], uint32_t wss, int c) {
    using R = Res<KR>;
    const int n = (WHAT & 2) + (c >= 7);
#pragma unroll
    for (int kk = 0; kk < 4; kk++) {
        const int ks = c * 4 + kk;
        uint64_t dx = 0;
        if (WHAT != 1 || !R::ss(ks)) dx = wk[n].to(P.dX[n + (KR == KRQ ? 0 : 4)], x_slot(c) / 16 + kk * 2);
        if (WHAT & 2) wg_ss64<0>(dk, wk[4].to(P.dXk, m_pos(c) * 512 + kk * 128), dx, ks > 0);
        if ((WHAT & 1) && !R::ss(ks)) wg_rs64<0>(d, w[R::reg(ks)], dx, ks > 0);
        if ((WHAT & 1) && R::ss(ks)) wg_ss64<0>(d, mkdesc(wss + (ks - R::S0) * 2048, 1024, 1024, 1), mkdesc(x_slot(c) + kk * 32, 1024, 1024, 1), 1);
    }
}
__device__ __forceinline__ void x_wait(uint32_t sb, int c, uint32_t par) {
    if (c == 0 || c == 2 || c == 4 || c == 5 || c == 7) mbar_wait(sb + E_BAR + (B_XF + c) * 8, par);
    wg_fence();
}
template <bool VPERM> __device__ __forceinline__ uint32_t tile_row(int tid, int rank) {
    const int w = (tid >> 5) & 3, g = (tid >> 2) & 7;
    return (rank * 64 + (VPERM ? (w >> 1) * 32 + (g >> 1) * 8 + (w & 1) * 4 + (g & 1) : w * 16 + g)) * 16;
}
template <bool VPERM>
__device__ __forceinline__ void put_mem(const float* d, uint32_t a, int rank, uint32_t peer_off, uint32_t mb) {
    const uint32_t p0 = pack2(d[0], d[1]), p1 = pack2(d[2], d[3]), p2 = pack2(d[4], d[5]), p3 = pack2(d[6], d[7]);
    constexpr int R = VPERM ? 32 : 128;
    st_async32(a + peer_off, rank ? p0 : p2, mb + peer_off);
    st_async32(a + R + peer_off, rank ? p1 : p3, mb + peer_off);
    sts32(a, rank ? p2 : p0);
    sts32(a + R, rank ? p3 : p1);
}
#define XCOL(c) "r"(pack2(e[16 * c], e[16 * c + 1])), "r"(pack2(e[16 * c + 4], e[16 * c + 5])), "r"(pack2(e[16 * c + 8], e[16 * c + 9])), "r"(pack2(e[16 * c + 12], e[16 * c + 13]))
template <int R>
__device__ __forceinline__ void park_x(const float* d, uint32_t a0, uint32_t a1) {
#pragma unroll
    for (int h = 0; h < 2; h++) {
        const float* e = d + 2 * h;
        asm volatile("st.shared.v4.b32 [%8], {%0,%1,%2,%3}; st.shared.v4.b32 [%9], {%4,%5,%6,%7};"
                     :: XCOL(0), XCOL(1), "r"(a0 + h * R), "r"(a1 + h * R) : "memory");
    }
}
#undef XCOL
__device__ __forceinline__ void warp_arrive(uint32_t b) { __syncwarp(); if ((threadIdx.x & 31) == 0) mbar_arrive(b); }

__device__ __forceinline__ void x_load(uint32_t sb, const uint8_t* img, int c) {
    const uint32_t bytes = c == 4 ? 8192 : 16384;
    mbar_expect(sb + E_BAR + (B_XF + c) * 8, bytes);
    bulk_g2s(sb + x_slot(c), img + c * 8192, bytes, sb + E_BAR + (B_XF + c) * 8);
}
__device__ __forceinline__ void x_ready(const uint32_t* f, uint32_t target) {
    asm volatile("{.reg .pred p; .reg .b32 v; W: ld.relaxed.gpu.global.u32 v, [%0]; sub.s32 v, v, %1; setp.lt.s32 p, v, 0; @p bra W;}" :: "l"(f), "r"(target) : "memory");
    fence_acq_gpu();
    fence_async_glb();
}

template <int N>
__device__ __forceinline__ uint32_t reduce_unit(const CUtensorMap* tm, int x, int y, uint32_t buf, uint32_t mb, uint32_t& ph, uint32_t tag, int lane, int& n, uint32_t prof_at) {
#pragma unroll 1
    while (true) {
        if (N == 16 && elect()) { mbar_expect(mb, N * 128); tma_2d(buf, tm, x, y, mb); }
        mbar_wait(mb, ph);
        ph ^= 1;
        float a[4];
        uint32_t v[N];
#pragma unroll
        for (int j = 0; j < N; j++) v[j] = lds32(buf + lane * 4 + j * 128);
#pragma unroll
        for (int j = 0; j < N; j++) {
            const int k = N == 16 ? 2 * (j & 1) : 0;
            a[k] = j < N / 8 ? bf_lo(v[j]) : a[k] + bf_lo(v[j]);
            a[k + 1] = j < N / 8 ? bf_hi(v[j]) : a[k + 1] + bf_hi(v[j]);
        }
        uint32_t bad = or3(xor_or(v[0], v[1], tag), xor_or(v[2], v[3], tag), xor_or(v[4], v[5], tag));
        if (N == 16) {
            bad = or3(bad, or3(xor_or(v[6], v[7], tag), xor_or(v[8], v[9], tag), xor_or(v[10], v[11], tag)), xor_or(v[12], v[13], tag));
            a[0] += a[2]; a[1] += a[3];
        }
#pragma unroll
        for (int o = 16; o >= (N == 16 ? 16 : 4); o >>= 1) { a[0] += __shfl_xor_sync(~0u, a[0], o); a[1] += __shfl_xor_sync(~0u, a[1], o); }
        if (!(__ballot_sync(~0u, or_bit0(bad, xor_or(v[N - 2], v[N - 1], tag))) & 0x11111111u)) return pack2(a[0], a[1]);
        if (N == 8 && elect()) { mbar_expect(mb, N * 128); tma_2d(buf, tm, x, y, mb); }
        RETRY(n, 1);
    }
    return 0;
}
__device__ __forceinline__ uint32_t ag_place(int tile, int layer, int t, int up, bool writes) {
    const int f = (blockIdx.x >> 4) * 16 + ((blockIdx.x >> 1) & 7) + up * 8;
    return opaque((m_pos(tile) * 128 + layer * 64 + f) * 16 + t * 4 + (((f >> 3) & 3) == t) + (writes ? 0 : 2));
}
__device__ __forceinline__ uint32_t mem0_word(const Params& P, int tile, uint32_t ag_dst) {
    const uint16_t* m = (const uint16_t*)P.mem0 + tile * 64 + ((ag_dst >> 4) & 63) + ((ag_dst >> 2) & 3) * (2 * DM);
    return (uint32_t)__ldg(m) | ((uint32_t)__ldg(m + DM) << 16);
}
__device__ __forceinline__ void ag_store(uint8_t* to, uint32_t w, uint32_t ag_dst, uint32_t atag) {
    asm volatile("{.reg .pred p; setp.eq.u32 p, %2, 0; @p st.relaxed.gpu.global.u32 [%0], %1;}" :: "l"(to), "r"(tagged(w, ag_dst & 1, atag)), "r"(ag_dst & 2) : "memory");
}

__device__ __forceinline__ void engine_a(const Params& P, uint32_t sb) {
    const uint32_t bars = sb + E_BAR;
    uint32_t w[KRQ][4];
    load_wregs<KRQ, 0>(w, sb);
    const int rank = blockIdx.x & 1;
    const uint32_t peer_off = mapa(sb, rank ^ 1) - sb;
    const int tid = opaque(threadIdx.x);
    const bool warp0 = __shfl_sync(~0u, tid, 0) == 0, lane0 = (tid & 31) == 0;
    const uint32_t row = opaque(sb + tile_row<false>(tid, rank));
    const int dq = opaque((tid >> 2) - 2 * (tid & 3));
#pragma unroll 1
    for (int i = 0; i < NSTEP; i++) {
        {
            const uint32_t xp = i & 1;
            float xq[32], xk[32], d[8];
            Walk wk[5];
#define W(c) x_wait(sb, c, xp);
#define Q(c) proj_x<KRQ, 1>(P, wk, xq, xk, w, E_WQ, c);
#define K(c) proj_x<KRQ, 2>(P, wk, xq, xk, w, E_WQ, c);
#define B(c) proj_x<KRQ, 3>(P, wk, xq, xk, w, E_WQ, c);
#define C wg_commit();
#define E C wg_wait<1>(); if (lane0) mbar_arrive(bars + B_E01 * 8); ES(0, 8); wg_fence();
#define M C wg_wait<1>(); if (lane0) mbar_arrive(bars + B_MF * 8); ES(0, 9); wg_fence();
#define T C wg_wait<1>(); if (lane0) { mbar_arrive_remote(bars + B_TF * 8 + peer_off); mbar_arrive(bars + B_TF * 8); } wg_fence();
            if (i > 0) nbar_sync(NB_WIA, NTHREADS);
            XSEQ
#undef W
#undef Q
#undef K
#undef B
#undef C
#undef E
#undef M
#undef T
            nbar_arrive(NB_XI, 256);
            const uint32_t t = keep(tid) & 3, own = row + t * (2 * TG), out = row - rank * 1024 + E_OUT + t * SG, ownq = own + E_QX + (t ? 0 : TG);
            ES(0, 10);
            mbar_wait(bars + B_TF * 8, xp);
            wg_wait<KEARLY>();
            park_x<128>(xk, rank ? out : own + E_KX, rank ? own + E_KX : out);
            __syncwarp();
            wg_wait<0>();
            park_x<128>(xq, rank ? out + 1024 : ownq, rank ? ownq : out + 1024);
            fence_async_smem();
            __syncwarp();
            if (lane0) mbar_arrive(bars + B_RF * 8);
            ES(0, 11);
            mbar_wait(bars + B_ML * 8, xp);
            ES(0, 5);
            proj_mem<KRQ, true>(P.dMq, d, w, E_WQ);
            mbar_wait(bars + B_M * 8, xp);
            const bool redo = __shfl_sync(~0u, lds32(sb + E_REDO), 0) == i + 1;
            wg_wait<0>();
            if (redo) {
                proj_mem<KRQ, false>(P.dMq2, d, w, E_WQ);
                wg_wait<0>();
            }
            put_mem<false>(d, row + E_QM + t * 4, rank, peer_off, bars + B_QK * 8);
            __syncwarp();
            if (lane0) { mbar_expect(bars + B_QK * 8, (2048 + 12288) / 4); mbar_arrive(bars + B_PD * 8); }
        }
        const uint32_t par = i & 1;
        ES(0, 1);
        uint32_t pa[12];
        float s0, s1;
        uint32_t a, o_dst;
        {
            float s[20];
            constexpr float MASKED = -1e9f / SM_SCALE;
            const int dl = keep(warp0 ? 64 : dq);
#pragma unroll
            for (int j = 0; j < 20; j++) s[j] = j >= 16 || (j > 4 && (j & 2)) || (j >> 2) * 8 + (j & 1) <= (j & 2 ? dq : dl) ? 0.f : MASKED;
#pragma unroll
            for (int j = 3; j < 12; j++)
                if (j == 3 || j == 5 || j == 7 || j >= 10) asm volatile("lop3.b32 %0, %1, %2, %3, 0x28;" : "=r"(pa[j]) : "r"(dq), "r"(j), "r"(P.zero));
            {
                const int t = keep(tid);
                a = sb + E_OM + rank * 2048 + (t >> 2) * 128 + (((t ^ (t >> 2)) & 3) << 4) + (t & 16) * 4;
                o_dst = ((i & (RB - 1)) * 64 + (blockIdx.x & ~1)) * 8192 + rank * 2048 + (t >> 2) * 64 + (((t ^ (t >> 3)) & 3) << 4);
                pin(P, a | o_dst);
            }
            uint64_t da = P.dQ, db = P.dK;
            mbar_wait_cl(bars + B_QK * 8, par);
            CFENCE;
            ES(0, 2);
            wg_fence();
#pragma unroll
            for (int ks = 0; ks < 8; ks++) { wg_ss40<1>(s, da, db, 1); if (ks < 7) { dmove(da, 16); dmove(db, 16); } }
            wg_commit();
            nbar_arrive(NB_SI, 256);
            wg_wait<0>();
            if (lane0) mbar_arrive(bars + B_SD * 8);
            ES(0, 3);
            float m0 = fmaxf(fmaxf(fmaxf(s[0], s[1]), fmaxf(s[4], s[5])), fmaxf(fmaxf(fmaxf(s[8], s[9]), fmaxf(s[12], s[13])), fmaxf(s[16], s[17])));
            float m1 = fmaxf(fmaxf(s[2], s[3]), fmaxf(s[18], s[19]));
#pragma unroll
            for (int x = 1; x <= 2; x++) { m0 = fmaxf(m0, __shfl_xor_sync(~0u, m0, x)); m1 = fmaxf(m1, __shfl_xor_sync(~0u, m1, x)); }
            m0 *= SM_SCALE * LOG2E;
            m1 *= SM_SCALE * LOG2E;
#pragma unroll
            for (int j = 0; j < 20; j++) if (!(j & 2) || j < 4 || j >= 16) s[j] = ex2(fmaf(s[j], SM_SCALE * LOG2E, j & 2 ? -m1 : -m0));
#pragma unroll
            for (int m = 0; m < 5; m++) pa[2 * m] = pack2(s[4 * m], s[4 * m + 1]);
            pa[1] = pack2(s[2], s[3]);
            pa[9] = pack2(s[18], s[19]);
            s0 = ((s[0] + s[1]) + (s[4] + s[5])) + ((s[8] + s[9]) + (s[12] + s[13])) + (s[16] + s[17]);
            s1 = (s[2] + s[3]) + (s[18] + s[19]);
        }
        {
            float o[64];
            ES(0, 4);
            mbar_wait_cl(bars + B_V * 8, par);
            CFENCE;
            wg_fence();
#pragma unroll
            for (int u = 0; u < 2; u++) {
                wg_rs64<0>(o + 32 * u, &pa[0], mkdesc(E_VX + u * 1024, 2 * TG, 128, 0), 0);
                wg_rs64<0>(o + 32 * u, &pa[4], mkdesc(E_VX + u * 1024 + 4 * TG, 2 * TG, 128, 0), 1);
                wg_rs64<0>(o + 32 * u, &pa[8], mkdesc(E_VM + u * 1024, 0, 128, 0), 1);
                wg_commit();
            }
            nbar_arrive(NB_PVI, 256);
#define OCHUNK(jj) make_uint4(pack2(o[16 * (jj)], o[16 * (jj) + 1]), pack2(o[16 * (jj) + 4], o[16 * (jj) + 5]), pack2(o[16 * (jj) + 8], o[16 * (jj) + 9]), pack2(o[16 * (jj) + 12], o[16 * (jj) + 13]))
            const uint32_t one = lds32(sb + E_ONE);
            s0 += __shfl_xor_sync(~0u, s0, one); s1 += __shfl_xor_sync(~0u, s1, one);
            pin(P, __float_as_uint(s0) | __float_as_uint(s1));
            const float r0 = __shfl_xor_sync(~0u, s0, 2), r1 = __shfl_xor_sync(~0u, s1, 2);
            wg_wait<1>();
            ES(0, 6);
            if (warp0) { st_async128(a + peer_off, OCHUNK(0), bars + B_OM * 8 + peer_off); st_async128((a ^ 64) + peer_off, OCHUNK(1), bars + B_OM * 8 + peer_off); }
            float inv = rcp(s0 + r0);
            if (tid < 32 && !(tid & 3)) {
                st_async32(sb + E_INV + rank * 32 + tid + peer_off, __float_as_uint(inv), bars + B_OM * 8 + peer_off);
                sts32(sb + E_INV + rank * 32 + tid, __float_as_uint(inv));
            }
            __syncwarp();
            wg_wait<0>();
            if (warp0) {
                const uint4 m2 = OCHUNK(2), m3 = OCHUNK(3);
                st_async128(a + 1024 + peer_off, m2, bars + B_OM * 8 + peer_off);
                st_async128((a ^ 64) + 1024 + peer_off, m3, bars + B_OM * 8 + peer_off);
                sts128(a + 1024, m2); sts128((a ^ 64) + 1024, m3);
                sts128(a, OCHUNK(0)); sts128(a ^ 64, OCHUNK(1));
                __syncwarp();
                inv = rcp(s1 + r1);
            }
            if (lane0) mbar_expect(bars + B_OM * 8, (2048 + 32) / 4);
            ES(0, 7);
#pragma unroll
            for (int j = 0; j < 32; j++) o[(j >> 1) * 4 + (j & 1)] = (warp0 ? o[(j >> 1) * 4 + 2 + (j & 1)] : o[(j >> 1) * 4 + (j & 1)]) * inv;
#pragma unroll
            for (int jj = 0; jj < 4; jj++) stg128(g_o + o_dst + jj * 4096, OCHUNK(jj));
#undef OCHUNK
            nbar_arrive(NB_WIB, NTHREADS);
        }
    }
    mbar_wait(bars + B_OM * 8, (NSTEP - 1) & 1);
}

__device__ __forceinline__ void engine_b(const Params& P, uint32_t sb) {
    const uint32_t bars = sb + E_BAR;
    uint32_t w[KRV][4];
    load_wregs<KRV, 1>(w, sb);
    const int rank = blockIdx.x & 1;
    const uint32_t peer_off = mapa(sb, rank ^ 1) - sb;
    const int tid = threadIdx.x & 127, warp = __shfl_sync(~0u, tid >> 5, 0);
    const bool lane0 = opaque(tid & 31) == 0;
    const uint32_t am = opaque(sb + E_VM + tile_row<true>(tid, rank) + (tid & 3) * 4);
    uint32_t j0, j1 = ag_place(8, rank, tid & 3, warp & 1, (tid & 31) < 4), ph = 0;
    if (warp == 0) {
        const int kg = ((blockIdx.x & ~1) + tid) / 13;
        j0 = opaque((blockIdx.x & ~1) * 8192 + rank * 2048 + (tid >> 4) * 4096 + (tid & 15) * 128);
        j1 = opaque(tid == 0 || (tid == 1 && kg * 13 == (blockIdx.x | 1)) ? (F_O + kg) * sizeof(g_flag[0]) : 0);
    } else {
        j0 = mem0_word(P, 8, j1);
    }
    const uint32_t e1 = __shfl_sync(~0u, lds32(sb + E_EPOCH), 0) + 1;
    const uint8_t* img = g_xe;
    if (warp == 0) {
        x_ready(g_flag[F_XE][0], e1 * XE_COUNT);
        TV(128, 126, 8, gtl());
        fence_async_smem();
        if (elect()) { x_load(sb, img, 0); x_load(sb, img, 2); x_load(sb, img, 5); }
    }
#pragma unroll 1
    for (int i = 0; i < NSTEP; i++) {
        {
            const uint32_t xp = i & 1;
            float xv[32];
            Walk wk[2];
            static_assert(GB1 + GB2 >= 4 && GB1 + GB2 <= 6 && GB1 + GB2 + GB3 <= 7, "");
#define ORD(c) (c < 4 ? c : c < 6 ? c + 1 : 4)
#define XB(c) x_wait(sb, c, xp); proj_x<KRV, 1>(P, wk, xv, xv, w, E_WV, c); wg_commit()
#pragma unroll
            for (int c = 0; c < GB1; c++) { XB(c); }
            if (i > 0) nbar_sync(NB_PVI, 256);
#pragma unroll
            for (int c = GB1; c < GB1 + GB2; c++) { XB(ORD(c)); }
            ES(128, 14);
            if (warp == 0 && elect()) x_load(sb, img, 4);
            wg_wait<0>();
            if (lane0) { mbar_arrive(bars + B_E01 * 8); mbar_arrive(bars + B_MF * 8); }
            if (i > 0) nbar_sync(NB_WIB, NTHREADS);
#pragma unroll
            for (int c = GB1 + GB2; c < GB1 + GB2 + GB3; c++) { XB(ORD(c)); }
            if (i > 0) nbar_sync(NB_WIA, NTHREADS);
#pragma unroll
            for (int c = GB1 + GB2 + GB3; c < 7; c++) { XB(ORD(c)); }
            if (warp == 0) {
                if (i > 0) {
                    const uint8_t* o = g_o + ((i - 1) & (RB - 1)) * (64 * 8192) + j0;
                    if (RB_DELAY) spin_cycles(RB_DELAY);
                    const uint32_t v = ld_rlx((const uint32_t*)o) | ld_rlx((const uint32_t*)(o + 8192));
                    if (j1) flag_signal_after(P, (uint32_t*)((uint8_t*)g_flag[0][i - 1] + j1), v);
                    ES(0, 17);
                }
            } else if (warp == 1) {
                mbar_wait(bars + B_E01 * 8, xp);
                if (X7_DELAY) spin_cycles(X7_DELAY);
                if (elect()) x_load(sb, img, 7);
            } else {
                const uint32_t ra = (e1 - 1) * NSTEP + i, rr = ra - e1;
                uint32_t w9 = j0;
                if (i > 0) {
                    int n = 0;
                    const int l1 = fresh_tid() & 31;
                    ES(192, 12);
                    w9 = reduce_unit<8>(&P.tmR9, 1792 + rank * 256 + warp * 128 + (blockIdx.x >> 1) * 4, (rr & 1) * 64, sb + E_RS + 6144 + warp * 1024, bars + (B_R9 - 2 + warp) * 8, ph,
                                           ((rr >> 1) & 1) ^ 1, l1, n, sb + E_BAR + 128 + (xp ^ 1) * 128 + 29 * 4);
                    EV(192, 25, n);
                }
                if (rank && i == LAG) w9 = j0;
                ag_store(g_ag + ((ra & 1) * 18432 + (keep(j1) & ~3u)), w9, j1, ((ra >> 1) & 1) ^ 1);
                ES(192, 0);
            }
            ES(128, 28);
            wg_wait<0>();
            if (lane0) { mbar_arrive_remote(bars + B_TF * 8 + peer_off); mbar_arrive(bars + B_TF * 8); }
            nbar_sync(NB_XI, 256);
            XB(7); XB(8);
#undef XB
#undef ORD
            const uint32_t t = (keep(am) >> 2) & 3, own = am + t * (2 * TG - 4) + (E_VX - E_VM), out = am + t * (SG - 4) + (E_OUT + 2048 - E_VM) - rank * 1024;
            mbar_wait(bars + B_TF * 8, xp);
            wg_wait<0>();
            ES(128, 15);
            park_x<32>(xv, rank ? out : own, rank ? own : out);
            fence_async_smem();
            __syncwarp();
            if (lane0) mbar_arrive(bars + B_RF * 8);
            img += XIMG;
            if (warp == 1 && i < NSTEP - 1) x_ready(g_flag[F_XE][i + 1], e1 * XE_COUNT);
            if (warp < 2) {
                mbar_wait(bars + (B_EARLY ? B_ML : B_M) * 8, xp);
                mbar_wait(bars + B_RF * 8, xp);
                if (elect()) {
                    if (warp == 0) {
#pragma unroll 1
                        for (int j = 0; j < 4; j++) {
                            const uint32_t o = sb + j * (2 * TG) + rank * 1024 + peer_off;
                            bulk_s2peer(o + E_KX, sb + E_OUT + j * SG, 1024, bars + B_QK * 8 + peer_off);
                            bulk_s2peer(o + E_QX + (j ? 0 : TG), sb + E_OUT + j * SG + 1024, 1024, bars + B_QK * 8 + peer_off);
                            bulk_s2peer(o + E_VX, sb + E_OUT + j * SG + 2048, 1024, bars + B_QK * 8 + peer_off);
                        }
                    } else if (i < NSTEP - 1) {
                        x_load(sb, img, 0);
                    }
                }
            }
        }
        ES(128, 16);
        float d[8];
        nbar_sync(NB_QKI, NTHREADS);
        proj_mem<KRV, false>(P.dMv, d, w, E_WV);
        wg_wait<0>();
        put_mem<true>(d, am, rank, peer_off, bars + B_V * 8);
        __syncwarp();
        if (lane0) { mbar_expect(bars + B_V * 8, 1024 / 4); mbar_arrive(bars + B_PD * 8); }
        ES(128, 18);
        nbar_sync(NB_SI, 256);
    }
    nbar_sync(NB_PVI, 256);
    nbar_sync(NB_WIB, NTHREADS);
    if (warp == 0 && j1) flag_signal((uint32_t*)((uint8_t*)g_flag[0][NSTEP - 1] + j1));
}

__device__ __forceinline__ void engine_c(const Params& P, uint32_t sb) {
    const uint32_t bars = sb + E_BAR;
    const int e = blockIdx.x, rank = e & 1;
    const int tid = opaque(threadIdx.x & 127), lane = tid & 31, warp = __shfl_sync(~0u, tid >> 5, 0);
#pragma unroll 1
    for (int round = 0; round < 2; round++) {
        if (tid == 0) {
            fence_async_smem();
            mbar_expect(bars + B_WL * 8, (round ? KRQ + KRV - 2 * E_ST1 : 2 * E_ST1) * 2048);
            mbar_expect(bars + (round ? B_WO : B_WS) * 8, round ? 36 * 2048 : E_RING - 36 * 2048);
        }
        nbar_sync(NB_C, 128);
        const int j = round * E_ST1 + lane, k = tid - 64 - (warp - 2) * 14;
        if (warp == 0) {
            if (lane < E_ST1 && j < KRQ) tma_w(sb + e_stage(lane), &P.tmWq, Res<KRQ>::step(j), e, bars + B_WL * 8);
            if (!round && lane < 36 - KRQ) tma_w(sb + E_WQ + lane * 2048, &P.tmWq, S0Q + lane, e, bars + B_WS * 8);
        } else if (warp == 1) {
            if (lane < E_ST1 && j < KRV) tma_w(sb + e_stage(E_ST1 + lane), &P.tmWv, Res<KRV>::step(j), e, bars + B_WL * 8);
            if (!round && lane < 36 - KRV) tma_w(sb + E_WV + lane * 2048, &P.tmWv, S0V + lane, e, bars + B_WS * 8);
        } else {
            spin_cycles(1200);
            if (lane < 18) {
                if (!round) tma_w(sb + E_WK + (m_pos(k >> 2) * 4 + (k & 3)) * 2048, &P.tmWk, k, e, bars + B_WS * 8);
                else tma_w(sb + E_WO + k * 2048, &P.tmWo, k < 32 ? (e >> 1) * 8 + (k & 7) : e * 4 + k - 32, k < 32 ? rank * 4 + (k >> 3) : 8, bars + B_WO * 8);
            }
        }
        if (!round) nbar_sync(NB_ALL, NTHREADS);
    }
    cluster_wait();
    const uint32_t peer_off = mapa(sb, rank ^ 1) - sb;
    const uint32_t epoch = __shfl_sync(~0u, lds32(sb + E_EPOCH), 0);
    const uint32_t ag_dst = ag_place(rank * 4 + warp, (lane >> 1) & 1, (lane >> 2) & 3, lane & 1, lane < 16), w_init = mem0_word(P, rank * 4 + warp, ag_dst);
    const uint32_t k_dst = opaque(sb + E_KM + tile_row<false>(tid, rank) + (tid & 3) * 4);
    const bool lane0 = lane == 0;
    uint32_t rr = epoch * (NSTEP - 1) - 1, ra = epoch * NSTEP, ph = 0;
    mbar_wait(bars + B_WS * 8, 0);
#pragma unroll 1
    for (int i = -1; i < NSTEP; i++, rr++, ra++) {
        const uint32_t par = i & 1;
        uint32_t w0 = w_init, tf = 0;
        const uint32_t atag = ((ra >> 1) & 1) ^ 1;
        uint8_t* const ag_to = g_ag + ((ra & 1) * 18432 + (ag_dst & ~3u));
        if (i >= 0) {
            const uint32_t tag = ((rr >> 1) & 1) ^ 1;
            uint32_t mine, latest;
            {
                float d[8];
                uint64_t da = P.dWk, db = P.dMk;
#pragma unroll
                for (int j = 0; j < 8; j++) d[j] = 0.f;
#pragma unroll 1
                for (int p = P.zero; p < KLOOP; p++) {
                    wg_fence();
#pragma unroll
                    for (int j = 0; j < 36 / KLOOP; j++) { wg_ss16<1>(d, da, db, 1); dmove(da, 128); dmove(db, (j & 3) < 3 ? 16 : 80); }
                    wg_commit();
                }
                nbar_arrive(NB_QKI, NTHREADS);
                wg_wait<0>();
                put_mem<false>(d, k_dst, rank, peer_off, bars + B_QK * 8);
                __syncwarp();
                if (lane0) { mbar_arrive(bars + B_QK * 8); mbar_arrive(bars + B_PD * 8); }
                ES(256, 13);
                mbar_wait(bars + B_QK * 8, par);
                if (tid == 0) mbar_arrive_remote(bars + B_V * 8 + peer_off);
                if (i == NSTEP - 1) break;
                unsigned long long now;
                asm volatile("mov.u64 %0, %%globaltimer;" : "=l"(now));
                tf = clock32();
                if (tid == 0) asm volatile("red.relaxed.gpu.global.max.u64 [%0], %1;" :: "l"(&g_latest), "l"(now) : "memory");
                mine = (uint32_t)now;
                if (warp == 3) {
                    mbar_wait(bars + B_PD * 8, par);
                    if (elect()) x_load(sb, g_xe + (i + 1) * XIMG, 2);
                    mbar_wait(bars + B_SD * 8, par);
                    if (elect()) x_load(sb, g_xe + (i + 1) * XIMG, 5);
                    EFLUSH(i - 1);
                }
                mbar_wait(bars + B_WO * 8, 0);
                while ((int)(clock32() - tf) < LATE_WAIT) {}
                latest = ld_rlx((const uint32_t*)&g_latest);
            }
            {
                float y[4][8];
                uint64_t db = P.dOm + rank * 64, da = P.dWo + 32 * 128;
                const uint32_t inv_at = opaque(sb + E_INV + (tid & 3) * 8);
                uint8_t* const dst = g_rs + (size_t)opaque(((rr & 1) * NENG + e) * 10240 + tid * 16);
#define W_TILE(Y, F) { _Pragma("unroll") for (int ks = 0; ks < 8; ks++) { wg_ss16<0>(y[Y], da, db, ks > 0 ? 1 : F); dmove(da, 128); dmove(db, ks == 7 ? -70 : ks == 3 ? 58 : 2); } wg_commit(); }
#define WORD(Y, k) pack2(y[Y][2 * (k)] * __uint_as_float((k) < 2 ? i0.x : i1.x), y[Y][2 * (k) + 1] * __uint_as_float((k) < 2 ? i0.y : i1.y))
#define W_ST(Y, T) { st_rlx128(dst + (T) * 2048, make_uint4((WORD(Y, 0) & ~1u) | tag, WORD(Y, 1), WORD(Y, 2), WORD(Y, 3))); __syncwarp(); }
                mbar_wait_cl(bars + B_OM * 8, par);
                CFENCE;
                ES(256, 19);
                const uint2 i0 = lds64(inv_at), i1 = lds64(inv_at + 32);
                wg_fence();
#pragma unroll
                for (int ks = 0; ks < 4; ks++) { wg_ss16<0>(y[0], da, db, ks > 0); dmove(da, ks < 3 ? 128 : -35 * 128); if (ks < 3) dmove(db, 2); }
                wg_commit();
                db = P.dOm;
                W_TILE(1, 0);
                W_TILE(2, 0);
                wg_wait<2>();
#pragma unroll
                for (int k = 0; k < 4; k++) st_rlx32(dst + 8192 + k * 512 - tid * 12, tagged(WORD(0, k), (tid & 3) == 0, tag));
                __syncwarp();
                if (WIB_AT == 1) nbar_arrive(NB_WIB, NTHREADS);
                wg_fence();
                W_TILE(3, 0);
                wg_wait<2>(); W_ST(1, 0);
                if (WIB_AT == 2) nbar_arrive(NB_WIB, NTHREADS);
                wg_fence();
                W_TILE(0, -1);
                wg_wait<2>(); W_ST(2, 1);
                if (WIB_AT == 3) nbar_arrive(NB_WIB, NTHREADS);
                wg_wait<1>(); W_ST(3, 2);
                if (WIB_AT == 4) nbar_arrive(NB_WIB, NTHREADS);
                nbar_arrive(NB_WIA, NTHREADS);
                wg_wait<0>(); W_ST(0, 3);
#undef W_TILE
#undef W_ST
#undef WORD
            }
            const uint32_t t0 = clock32();
            ES(352, 20);
            const int w1 = keep(warp), x0 = rank * 2560 + w1 * 512 + (e >> 1) * 16;
            tf += min(max((int)(latest - mine), 0), 1000) * LATE_MUL / 4 + RS_AT;
            if ((int)(t0 + RS_DELAY - tf) > 0) tf = t0 + RS_DELAY;
            int n = 0;
            EV(0, 30, tf - t0);
            if (w1 >= 2) {
                while ((int)(clock32() - tf) < -RS_DELAY0) {}
                if (elect()) {
                    mbar_expect(bars + (B_R9 - 2 + w1) * 8, 1024);
                    tma_2d(sb + E_RS + 6144 + w1 * 1024, &P.tmR9, 1792 + rank * 256 + w1 * 128 + (e >> 1) * 4, (rr & 1) * 64, bars + (B_R9 - 2 + w1) * 8);
                }
            }
            while ((int)(clock32() - tf) < (w1 - 3) * RS_SKEW) {}
            w0 = reduce_unit<16>(&P.tmRs, x0, (rr & 1) * 32, sb + E_RS + w1 * 2048, bars + (B_RS + w1) * 8, ph, tag, keep(tid) & 31, n, sb + E_BAR + 128 + par * 128 + 21 * 4);
            EV(352, 26, n);
            if (i == LAG - 1 && (ag_dst & 1024)) w0 = w_init;
        }
        ag_store(ag_to, w0, ag_dst, atag);
        ES(352, 22);
        if (lane0) { mbar_arrive_remote(bars + B_TF * 8 + peer_off); mbar_arrive(bars + B_TF * 8); }
        const int w1 = keep(warp), l1 = keep(tid) & 31;
        const uint32_t dst = sb + E_MEM + w1 * 4608, mb = bars + (B_RS + w1) * 8, chk = dst + l1 * 16 + (l1 >> 3) * 4;
        const uint8_t* src = g_ag + ((ra & 1) * 18432 + w1 * 4608);
        const bool one = elect();
        mbar_wait(bars + B_MF * 8, par ^ 1);
        const uint32_t t1 = clock_after(nbar_any(NB_C, 128, 0));
        int n = 0;
        if (w1 == 0) {
            if (i < 0 || (int)(t1 + AG_DELAY - AG_AT - tf) > 0) tf = t1 + AG_DELAY - AG_AT;
            while ((int)(clock32() - tf) < AG_AT) {}
            if (one) { mbar_expect(bars + B_ML * 8, 18432); bulk_g2s(dst, src, 18432, bars + B_ML * 8); }
        }
        mbar_wait(bars + B_ML * 8, par ^ 1);
#pragma unroll 1
        while (true) {
            uint32_t v[9];
#pragma unroll
            for (int j = 0; j < 9; j++) v[j] = lds32(chk + j * 512);
            if (!__any_sync(~0u, or_bit0(xor_or(v[0], v[1], atag) | xor_or(v[2], v[3], atag) | xor_or(v[4], v[5], atag), xor_or(v[6], v[7], atag) | (v[8] ^ atag)))) break;
            if (one) { sts32(sb + E_REDO, i + 2); mbar_expect(mb, 4608); bulk_g2s(dst, src, 4608, mb); }
            RETRY(n, 2);
            mbar_wait(mb, ph);
            ph ^= 1;
        }
        ES(352, 23); EV(352, 27, n);
        if (one) {
            mbar_arrive(bars + B_M * 8);
            if (n) {
                unsigned long long now;
                asm volatile("mov.u64 %0, %%globaltimer;" : "=l"(now));
                asm volatile("red.relaxed.gpu.global.max.u64 [%0], %1;" :: "l"(&g_latest), "l"(now + LATE_NS) : "memory");
            }
        }
        nbar_sync(NB_C, 128);
    }
    nbar_arrive(NB_WIB, NTHREADS);
    if (e == 0 && tid == 0) g_epoch = lds32(sb + E_EPOCH) + 1;
}

enum { ST_WO = 0, ST_F2 = 1, ST_F1 = 2 };
template <int ST> struct Stage;
template <> struct Stage<ST_WO> { static constexpr int NKS = 52, NR0 = 37, NR1 = 45, NT1 = 1, NSLOT = 8, TB = 0; };
template <> struct Stage<ST_F2> { static constexpr int NKS = 58, NR0 = 37, NR1 = 45, NT1 = 1, NSLOT = 5, TB = 1; };
template <> struct Stage<ST_F1> { static constexpr int NKS = 36, NR0 = F1_NR, NR1 = F1_NR, NT1 = 2, NSLOT = F1_SLOTS, TB = 0; };
template <int ST> struct StageMap : Stage<ST> {
    using S = Stage<ST>;
    static constexpr int NCH = (S::NKS + 3) / 4;
    static constexpr int W0A = 0, W0B = W0A + (S::NKS - S::NR0) * 2048, W1A = W0B + S::NKS * 2048, W1B = W1A + (S::NKS - S::NR1) * 2048;
    static constexpr int RNG = W1B + (S::NT1 - 1) * S::NKS * 2048;
    static constexpr int ROWS = RNG + S::NSLOT * 8192;
    static_assert(ROWS + (ST == ST_F1 ? 3 * 6912 : 0) <= SM_BAR && (S::NR0 + S::NR1) * 2048 <= SM_BAR, "stage smem");
};
__host__ __device__ constexpr int rs_idx(int ks, int nr, int nks) { return ks * nr / nks; }
__host__ __device__ constexpr bool is_rs(int ks, int nr, int nks) { return rs_idx(ks + 1, nr, nks) > rs_idx(ks, nr, nks); }

template <int ST, int SHAPE, int N, int NR>
__device__ __forceinline__ void stage_rounds(const Params& P, uint32_t sb, int idx, const int WG, const uint32_t (&w)[NR][4], int j0, int j1, uint32_t& s, uint32_t& ph) {
    using M = StageMap<ST>;
    constexpr int NT = SHAPE ? M::NT1 : 2, NKS = M::NKS, M0 = ST == ST_WO && N == 32 ? 4 : 0;
    const uint32_t bars = sb + SM_BAR;
    const bool shortk = ST != ST_F1 && idx >= 12;
    uint32_t use = __shfl_sync(~0u, lds32(sb + SM_EPOCH), 0) * NSTEP + j0;
#pragma unroll 1
    for (int j = j0; j < j1; j++, use++) {
        float d[NT][N / 2];
        uint64_t da0 = P.d128 + WG * (M::W1A / 16), da1 = da0 + (NKS - NR) * 128;
        uint32_t prev = 0;
#pragma unroll
        for (int c = 0; c < M::NCH; c++) {
            if (c < M::NCH - 1 || !shortk) {
                mbar_wait(bars + (B_FULL + s) * 8, ph);
                if (c == 0) TS(WG * 128, j, WG * 4);
                uint64_t b = (ST == ST_WO ? P.d64 : P.d128) + (M::RNG / 16 + s * 512 + (ST == ST_WO && N == 32 ? 128 : 0));
                wg_fence();
#pragma unroll
                for (int kk = 0; kk < 4; kk++) {
                    const int ks = c * 4 + kk;
                    if (ks < NKS) {
                        if (is_rs(ks, NR, NKS)) { if (N == 64) wg_rs64<M::TB>(d[0], w[rs_idx(ks, NR, NKS)], b, ks > 0); else wg_rs32<M::TB>(d[0], w[rs_idx(ks, NR, NKS)], b, ks > 0); }
                        else { if (N == 64) wg_ss64<M::TB>(d[0], da0, b, ks > 0); else wg_ss32<M::TB>(d[0], da0, b, ks > 0); dmove(da0, 128); }
                        if (NT > 1) { if (N == 64) wg_ss64<M::TB>(d[NT - 1], da1, b, ks > 0); else wg_ss32<M::TB>(d[NT - 1], da1, b, ks > 0); dmove(da1, 128); }
                        if (kk < 3) dmove(b, ST == ST_WO ? (kk == 1 ? 254 : 2) : M::TB ? 128 : 2);
                    }
                }
                wg_commit();
                if (c > 0) {
                    wg_wait<1>();
                    if ((fresh_tid() & 31) == 0) mbar_arrive(prev);
                }
                prev = bars + (B_EMPTY + s) * 8;
                if (++s == M::NSLOT) { s = 0; ph ^= 1; }
            }
        }
        const int tid = fresh_tid(), g = (tid >> 2) & 7, t = tid & 3, warp = (tid >> 5) & 3;
        wg_wait<0>();
        if ((tid & 31) == 0) mbar_arrive(prev);
        TS(WG * 128, j, WG * 4 + 1);
        if (ST == ST_F1) {
            uint8_t* dst = g_h + ((j & (RB - 1)) * FF + idx * 128 + WG * 64 + warp * 16 + g) * 128;
#pragma unroll
            for (int h = 0; h < 2; h++) {
#pragma unroll
                for (int c = 0; c < N / 32; c++) {
                    uint32_t pk[4];
#pragma unroll
                    for (int m = 0; m < 4; m++) {
                        const int o = 16 * c + 4 * m + 2 * h;
                        const float g0 = d[0][o], g1 = d[0][o + 1];
                        const float e0 = 1.f + ex2(fminf(-LOG2E * g0, 60.f)), e1 = 1.f + ex2(fminf(-LOG2E * g1, 60.f));
                        const float r = rcp(e0 * e1);
                        pk[m] = pack2(g0 * d[NT - 1][o] * (e1 * r), g1 * d[NT - 1][o + 1] * (e0 * r));
                    }
                    stg128(dst + h * 1024 + (((c * 4 + t) ^ g) << 4), make_uint4(pk[0], pk[1], pk[2], pk[3]));
                }
            }
            TS(WG * 128, j, WG * 4 + 2);
            __syncwarp();
            const uint32_t z = nbar_any(NB_WG0 + WG, 128, ld_rlx((const uint32_t*)(dst + (t & 1) * 1024)) & P.zero);
            const int f0 = idx * 128 + WG * 64, kg = (f0 + (tid & 1) * 63) / 928;
            if ((tid & 127) == 0 || ((tid & 127) == 1 && kg * 928 > f0)) red_add_u32(g_flag[F_H + kg][j], z + 1);
            TS(WG * 128, j, WG * 4 + 3);
        } else {
            uint8_t* dst = g_part[ST & 1] + (((use & (RB - 1)) * 64 + g) * 5 + idx / 3) * 1152 + ((idx % 3) * 3 + WG) * 128 + warp * 32 + t * 8;
            const uint32_t tag = ((use / RB) & 1) ^ 1, tm = ~t & 1;
#pragma unroll
            for (int m = 0; m < N / 8; m++) {
#pragma unroll
                for (int T = 0; T < NT; T++)
                    st_rlx64(dst + T * 256 + (m + M0) * (8 * 5760), tagged(movm(pack2(d[T][4 * m], d[T][4 * m + 1])), tm, tag), movm(pack2(d[T][4 * m + 2], d[T][4 * m + 3])));
            }
            warp_arrive(bars + B_PUB * 8);
            if (N == 32) {
#pragma unroll 1
                for (int m = 0; m < 4 * NT; m++) st_rlx64(dst + (m >> 2) * 256 + ((m & 3) + 4 - M0) * (8 * 5760), tag, 0);
            }
            TS(WG * 128, j, WG * 4 + 2);
        }
    }
}
template <int ST, int SHAPE>
__device__ __forceinline__ void stage_consumer(const Params& P, uint32_t sb, int idx, const int WG) {
    using M = StageMap<ST>;
    constexpr int NR = SHAPE ? M::NR1 : M::NR0;
    const uint32_t bars = sb + SM_BAR;
    uint32_t w[NR][4];
    {
        const uint32_t base = frag_addr(sb + WG * (M::NR0 * 2048));
        mbar_wait(bars + B_WL * 8, 0);
#pragma unroll
        for (int r = 0; r < NR; r++) ldsm4t(w[r], base + r * 2048);
        TV(0, 126, 4, gtl());
        nbar_sync(NB_ALL, 288);
        mbar_wait(bars + B_WS * 8, 0);
        TV(0, 126, 7, gtl());
    }
    uint32_t s = 0, ph = 0;
    constexpr int WIDE = NARROW ? NSEG + (ST != ST_WO) : NSTEP;
    stage_rounds<ST, SHAPE, 64>(P, sb, idx, WG, w, 0, WIDE, s, ph);
    if (NARROW) stage_rounds<ST, SHAPE, 32>(P, sb, idx, WG, w, WIDE, NSTEP, s, ph);
}

template <int ST>
__device__ __forceinline__ void stage_producer(const Params& P, uint32_t sb, int idx) {
    using M = StageMap<ST>;
    const uint32_t bars = sb + SM_BAR;
    const int lane = threadIdx.x & 31;
    const int kg = ST == ST_F1 ? 0 : idx / 3;
    {
        const CUtensorMap* tm0 = ST == ST_WO ? &P.tmWo : ST == ST_F2 ? &P.tmW2 : &P.tmW1;
        const CUtensorMap* tm1 = ST == ST_F1 ? &P.tmW3 : tm0;
        const int k0 = kg * M::NKS, g0 = ST == ST_F1 ? idx * 2 : (idx % 3) * 3;
        constexpr int PACE = ST == ST_WO ? WO_PACE : ST == ST_F1 ? F1_PACE : F2_PACE;
        spin_cycles(ST == ST_WO ? WO_DELAY : G_DELAY);
        if (lane == 0) mbar_expect(bars + B_WL * 8, (M::NR0 + M::NR1) * 2048);
        __syncwarp();
#pragma unroll 1
        for (int ks = lane; ks < M::NKS + lane; ks += 4) {
            if (lane < 4 && ks < M::NKS) {
                if (is_rs(ks, M::NR0, M::NKS)) tma_w(sb + rs_idx(ks, M::NR0, M::NKS) * 2048, tm0, k0 + ks, g0, bars + B_WL * 8);
                if (is_rs(ks, M::NR1, M::NKS)) tma_w(sb + (M::NR0 + rs_idx(ks, M::NR1, M::NKS)) * 2048, tm0, k0 + ks, g0 + 1, bars + B_WL * 8);
            }
            __syncwarp();
            if (PACE) spin_cycles(PACE);
        }
        nbar_sync(NB_ALL, 288);
        if (lane == 0) { fence_async_smem(); mbar_expect(bars + B_WS * 8, M::RNG); }
        __syncwarp();
#pragma unroll 1
        for (int ks = lane; ks < M::NKS + lane; ks += 4) {
            if (lane < 4 && ks < M::NKS) {
                if (!is_rs(ks, M::NR0, M::NKS)) tma_w(sb + M::W0A + (ks - rs_idx(ks, M::NR0, M::NKS)) * 2048, tm0, k0 + ks, g0, bars + B_WS * 8);
                if (!is_rs(ks, M::NR1, M::NKS)) tma_w(sb + M::W1A + (ks - rs_idx(ks, M::NR1, M::NKS)) * 2048, tm0, k0 + ks, g0 + 1, bars + B_WS * 8);
                tma_w(sb + M::W0B + ks * 2048, tm1, k0 + ks, ST == ST_F1 ? g0 : g0 + 2, bars + B_WS * 8);
                if (ST == ST_F1) tma_w(sb + M::W1B + ks * 2048, tm1, k0 + ks, g0 + 1, bars + B_WS * 8);
            }
            __syncwarp();
            if (PACE) spin_cycles(PACE);
        }
    }
    if (lane != 0) return;
    const uint32_t e1 = lds32(sb + SM_EPOCH) + 1;
#define ROWS(u) ((u) > LAG && (u) <= NSEG ? 64 : 32)
#define XF_COUNT(u) (ROWS(u) + ((u) >= RB ? NF2 : 0))
    const int nch = M::NCH - (kg == 4);
    uint32_t s = 0, ph = 1;
#pragma unroll 1
    for (int j = 0; j < NSTEP; j++) {
        const int slot = j & ((ST == ST_F1 ? RING : RB) - 1);
        const uint8_t* src = ST == ST_F1 ? g_xf + slot * XIMG : ST == ST_WO ? g_o + (slot * 64 + kg * 13) * 8192 : g_h + (slot * FF + kg * 928) * 128;
        if (ST == ST_WO && j >= RB) flag_poll(g_flag[F_XF][j - RB + 1], e1 * XF_COUNT(j - RB + 1));
        if (ST == ST_F2 && j >= RB) flag_poll(g_flag[F_L2][j - RB], e1 * ROWS(j - RB));
        flag_poll(g_flag[ST == ST_F1 ? F_XF : (ST == ST_WO ? F_O : F_H) + kg][j], e1 * (ST == ST_F1 ? XF_COUNT(j) : ST == ST_WO ? (kg < 4 ? 14 : 12) : (kg < 4 ? 15 : 14)));
        fence_acq_gpu();
        fence_async_glb();
        TS(256, j, 8);
#pragma unroll 1
        for (int c = 0; c < nch; c++) {
            const uint32_t bytes = (ST == ST_F2 && c == M::NCH - 1) ? 4096 : 8192;
            mbar_wait(bars + (B_EMPTY + s) * 8, ph);
            mbar_expect(bars + (B_FULL + s) * 8, bytes);
            bulk_g2s(sb + M::RNG + s * 8192, src + c * 8192, bytes, bars + (B_FULL + s) * 8);
            if (++s == M::NSLOT) { s = 0; ph ^= 1; }
        }
    }
}

#undef XF_COUNT
#undef ROWS

template <int ST>
__device__ __forceinline__ void stage_split(const Params& P, uint32_t sb, int wg, int idx) {
    if (wg == 0) { reg_inc<240>(); stage_consumer<ST, 0>(P, sb, idx, 0); }
    else if (wg == 1) { reg_inc<240>(); stage_consumer<ST, 1>(P, sb, idx, 1); }
    else {
        reg_dec<24>();
        const int tid = fresh_tid();
        if (tid < 288) stage_producer<ST>(P, sb, idx);
        else if (tid == 288) {
#pragma unroll 1
            for (int j = 0; j < NSTEP; j++) {
                mbar_wait(sb + SM_BAR + B_PUB * 8, j & 1);
                red_add_u32(g_flag[F_PW + ST][j], 1);
                if (j + RB < NSTEP) red_add_u32(g_flag[ST == ST_WO ? F_XE : F_XF][j + RB], 1);
                TS(288, j, 9);
            }
        }
    }
}

#define NOG
__global__ void __cluster_dims__(2, 1, 1) __launch_bounds__(NTHREADS, 1) fused_kernel(const __grid_constant__ Params P) {
    extern __shared__ __align__(1024) uint8_t smem_raw[];
    const uint32_t sb = smem_u32(smem_raw);
    const int tid = threadIdx.x;
    const int wg = __shfl_sync(~0u, tid >> 7, 0);
    const int bid = blockIdx.x;
    if (tid == 0) {
        const uint32_t bars = sb + (bid < NENG ? E_BAR : SM_BAR);
        if ((sb & 0xffffff) != SM_BASE) __trap();
        TV(0, 126, 0, gtl()); TS(0, 126, 1);
        sts32(bars + 388, 1);
        if (bid < NENG) sts32(sb + E_REDO, 0);
        sts32(bars + 384, *(volatile uint32_t*)&g_epoch);
        for (int i = 0; i < 11; i++) mbar_init(bars + i * 8, 1);
        mbar_init(bars + B_QK * 8, 8); mbar_init(bars + B_V * 8, 5); mbar_init(bars + B_OM * 8, 4);
        mbar_init(bars + B_E01 * 8, 8); mbar_init(bars + B_TF * 8, 24);
        for (int i = 0; i < 8; i++) mbar_init(bars + (B_EMPTY + i) * 8, 8);
        mbar_init(bars + B_PUB * 8, 8);
        if (bid < NENG) { mbar_init(bars + B_RF * 8, 8); mbar_init(bars + B_PD * 8, 12); mbar_init(bars + B_MF * 8, 8); mbar_init(bars + B_M * 8, 4); }
        for (int i = 0; i < 12; i++) mbar_init(bars + (B_R9 + i) * 8, bid < NENG && B_R9 + i == B_SD ? 4 : 1);
        asm volatile("fence.mbarrier_init.release.cluster;" ::: "memory");
    }
    if (bid >= NENG) {
#pragma unroll 1
        for (int v = (bid - NENG) * NTHREADS + tid; v < (2 * LAG + (LAG < RING ? LAG + 1 : RING)) * 2304; v += (NGRID - NENG) * NTHREADS) {
            const int im = v / 2304, o = (v % 2304 >> 8) * 8192 + (v & 255) * 16;
            stg128((im < LAG ? g_xe + im * XIMG + 4096 : im < 2 * LAG ? g_xe + (im - LAG + NSEG) * XIMG : g_xf + (im - 2 * LAG) * XIMG + 4096) + o, make_uint4(0, 0, 0, 0));
        }
    }
    __syncthreads();
    if (bid < NENG) {
        cluster_arrive();
        if (wg == 0) { reg_inc<240>(); engine_a(P, sb); }
        else if (wg == 1) { reg_inc<200>(); engine_b(P, sb); }
        else { reg_dec<64>(); engine_c(P, sb); }
        TV(0, 126, 2, gtl()); TS(0, 126, 3);
        cluster_sync_all();
    } else if (bid < CTA_WO) {
        const int idx = bid - CTA_F1;
        if (wg < 2) { NOG; reg_inc<92 + 4 * F1_NR>(); stage_consumer<ST_F1, 0>(P, sb, idx, wg); }
        else {
            reg_dec<504 - 2 * (92 + 4 * F1_NR)>();
            const int w = __shfl_sync(~0u, (fresh_tid() >> 5) & 3, 0);
            if (w == 0) {
                NOG;
                stage_producer<ST_F1>(P, sb, idx);
            } else {
                if ((tid & 31) == 0) red_add_u32(g_flag[F_DONE][0], 1);
                ln_first(P, (w - 1) * NF1 + idx, LN0_SPLIT, 3 * NF1);
                if (idx < 32) {
                    const uint32_t epoch = __shfl_sync(~0u, lds32(sb + SM_EPOCH), 0);
                    uint32_t ph = 0;
#pragma unroll 1
                    for (int j = w == 3 ? LAG : 0; j < (w == 3 ? NSEG : NSTEP); j++) {
                        if (w == 3) mbar_wait(sb + SM_BAR + B_R9 * 8, (j - LAG) & 1);
                        ln_job(P, w == 2, j, w == 3, idx, epoch, sb + StageMap<ST_F1>::ROWS + (w - 1) * 6912, sb + SM_BAR + (B_R9 + w) * 8, ph);
                        if (w == 1 && j >= LAG && elect()) mbar_arrive(sb + SM_BAR + B_R9 * 8);
                    }
                    TV(320, 126, 2, gtl());
                }
                return;
            }
        }
    } else if (bid < CTA_SP) {
NOG;
        if (bid < CTA_F2) stage_split<ST_WO>(P, sb, wg, bid - CTA_WO);
        else stage_split<ST_F2>(P, sb, wg, bid - CTA_F2);
    } else {
        const int w = (bid - CTA_SP) * 12 + (tid >> 5);
        if (bid == CTA_SP && tid < NSTEP) red_add_u32(g_flag[F_XE][tid], XE_COUNT - 32 * ((tid < NSEG) + (tid >= LAG) + (tid > 2 * LAG + 1)) - NWO * (tid >= RB));
        ln_first(P, LN0_SPLIT + w, S_TOK, 24);
        const uint32_t e1 = lds32(sb + SM_EPOCH) + 1;
        uint32_t ph = 0;
#pragma unroll 1
        for (int item = (LAG + 1) * 32 + w; item < (NSEG + 1) * 32; item += 24) {
            ln_job(P, 1, item >> 5, 1, item & 31, e1 - 1, sb + (tid >> 5) * 6912, sb + SM_BAR + (B_R9 + (tid >> 5)) * 8, ph);
        }
        TV(0, 126, 2, gtl()); TS(0, 126, 3);
        if (w == 23 && (tid & 31) == 0) {
            int n = 0;
            while ((int)(ld_rlx(g_flag[F_DONE][0]) - e1 * (CTA_SP * 12)) < 0) { SPIN_CHECK(n, 8); }
        }
        return;
    }
    __syncwarp();
    if ((fresh_tid() & 31) == 0) red_add_u32(g_flag[F_DONE][0], 1);
}

typedef CUresult (*EncodeFn)(CUtensorMap*, CUtensorMapDataType, cuuint32_t, void*, const cuuint64_t*, const cuuint64_t*,
                             const cuuint32_t*, const cuuint32_t*, CUtensorMapInterleave, CUtensorMapSwizzle,
                             CUtensorMapL2promotion, CUtensorMapFloatOOBfill);

void make_map(EncodeFn enc, CUtensorMap* m, const void* p, int rows, int cols) {
    cuuint64_t dims[3] = {64, (cuuint64_t)rows, (cuuint64_t)(cols / 64)};
    cuuint64_t strides[2] = {(cuuint64_t)cols * 2, 128};
    cuuint32_t box[3] = {64, 16, 1};
    cuuint32_t es[3] = {1, 1, 1};
    enc(m, CU_TENSOR_MAP_DATA_TYPE_BFLOAT16, 3, (void*)p, dims, strides, box, es, CU_TENSOR_MAP_INTERLEAVE_NONE,
        CU_TENSOR_MAP_SWIZZLE_128B, PROMO, CU_TENSOR_MAP_FLOAT_OOB_FILL_NONE);
}

void make_map2(EncodeFn enc, CUtensorMap* m, void* p, int words, int rows, int bw, int br) {
    cuuint64_t dims[2] = {(cuuint64_t)words, (cuuint64_t)rows};
    cuuint64_t strides[1] = {(cuuint64_t)words * 4};
    cuuint32_t box[2] = {(cuuint32_t)bw, (cuuint32_t)br};
    cuuint32_t es[2] = {1, 1};
    enc(m, CU_TENSOR_MAP_DATA_TYPE_UINT32, 2, p, dims, strides, box, es, CU_TENSOR_MAP_INTERLEAVE_NONE,
        CU_TENSOR_MAP_SWIZZLE_NONE, CU_TENSOR_MAP_L2_PROMOTION_NONE, CU_TENSOR_MAP_FLOAT_OOB_FILL_NONE);
}

}

extern "C" void kernel_launch(void* const* d_in, const int* in_sizes, int n_in, void* d_out, int out_size) {
    (void)in_sizes; (void)n_in; (void)out_size;
    static EncodeFn enc = nullptr;
    static void* rs = nullptr;
    if (!enc) {
        void* fn = nullptr;
        cudaDriverEntryPointQueryResult qr;
        cudaGetDriverEntryPoint("cuTensorMapEncodeTiled", &fn, cudaEnableDefault, &qr);
        enc = (EncodeFn)fn;
        cudaGetSymbolAddress(&rs, g_rs);
        cudaFuncSetAttribute(fused_kernel, cudaFuncAttributeMaxDynamicSharedMemorySize, SM_TOTAL);
    }
    Params P;
    make_map(enc, &P.tmWq, d_in[2], DM, 4096);
    make_map(enc, &P.tmWk, d_in[3], DM, 4096);
    make_map(enc, &P.tmWv, d_in[4], DM, 4096);
    make_map(enc, &P.tmWo, d_in[5], 4096, DM);
    make_map(enc, &P.tmW1, d_in[8], DM, FF);
    make_map(enc, &P.tmW3, d_in[9], DM, FF);
    make_map(enc, &P.tmW2, d_in[10], FF, DM);
    make_map2(enc, &P.tmRs, rs, 5120, 64, 16, 32);
    make_map2(enc, &P.tmR9, rs, 2560, 128, 4, 64);
    P.d128 = mkdesc(0, 1024, 1024, 1);
    P.d64 = mkdesc(0, 16, 512, 2);
    P.dX[0] = P.dX[1] = P.dX[2] = P.dX[3] = P.dX[4] = P.dX[5] = P.d128;
    P.dXk = P.dWk = P.d128 + E_WK / 16;
    P.dWo = P.d128 + E_WO / 16;
    P.dMq = P.dMq2 = P.dMk = P.dMv = mkdesc(E_MEM, 128, 1024, 0);
    P.dOm = mkdesc(E_OM, 16, 2048, 1);
    P.dQ = mkdesc(E_QX, 128, TG, 0);
    P.dK = mkdesc(E_KX, 128, 2 * TG, 0);
    P.zero = 0;
    P.x = (const bf16*)d_in[0];
    P.mem0 = (const bf16*)d_in[1];
    P.out = (bf16*)d_out;
    fused_kernel<<<NGRID, NTHREADS, SM_TOTAL>>>(P);
}
```
